```python
import torch

def _softmax(x, axis=-1):
    return torch.softmax(x, dim=axis)
def _gelu(x):
    return torch.nn.functional.gelu(x, approximate="tanh")
def _silu(x):
    return torch.nn.functional.silu(x)
def _sigmoid(x):
    return torch.sigmoid(x)
def _layernorm(x, axis=-1, eps=1e-5):
    m = x.mean(dim=axis, keepdim=True)
    v = x.var(dim=axis, keepdim=True, unbiased=False)
    return (x - m) / torch.sqrt(v + eps)
def _scatter_add(tgt, idx, src, axis=0):
    return tgt.clone().index_add_(axis, idx, src)
def _segment_sum(src, seg, n):
    out = torch.zeros((n,) + src.shape[1:], dtype=src.dtype)
    return out.index_add_(0, seg, src)
def _pad(x, pw):
    flat = tuple(v for pair in reversed(pw) for v in pair)
    return torch.nn.functional.pad(x, flat)

kernel_name = 'gated_mix__linear_kernel_hedgehog__mha_block__prompt'

def setup_inputs():

    _w = (lambda a: (lambda t: t.to(torch.bfloat16) if t.is_floating_point() else t)(torch.as_tensor(a)))
    def _A_setup():
        B, S, D, H = 1, 2048, 1024, 32
        Dh = D // H
        return {
            "x": _w((lambda *s: torch.randn(*s, dtype=torch.bfloat16) * 0.05)(B, S, D)),
            "wqkv": _w((lambda *s: torch.randn(*s, dtype=torch.bfloat16) * 3.2)(D, 3 * D)),
            "w_phi": _w((lambda *s: torch.randn(*s, dtype=torch.bfloat16) * 3.2)(H, Dh, Dh) * (Dh ** -0.5)),
            "wo": _w((lambda *s: torch.randn(*s, dtype=torch.bfloat16) * 1.6)(D, D)),
        }
    _A_in = _A_setup()

    def _B_setup():
        B, S, D, H = 1, 2048, 1024, 32
        return {
            "x": _w((lambda *s: torch.randn(*s, dtype=torch.bfloat16) * 0.05)(B, S, D)),
            "wqkv": _w((lambda *s: torch.randn(*s, dtype=torch.bfloat16) * 3.2)(D, 3 * D)),
            "wo": _w((lambda *s: torch.randn(*s, dtype=torch.bfloat16) * 0.1)(D, D)),
        }
    _B_in = _B_setup()

    return {
        "A_x": _A_in["x"],
        "A_wqkv": _A_in["wqkv"],
        "A_w_phi": _A_in["w_phi"],
        "A_wo": _A_in["wo"],
        "B_x": _B_in["x"],
        "B_wqkv": _B_in["wqkv"],
        "B_wo": _B_in["wo"],
        "gate_w": _w((lambda *s: torch.randn(*s, dtype=torch.bfloat16) * 0.4)(1024) * 16.0),
    }

def reference(A_x, A_wqkv, A_w_phi, A_wo, B_x, B_wqkv, B_wo, gate_w):
    def _A_ref(x, wqkv, w_phi, wo):
        B, S, D = x.shape
        H = 32; Dh = D // H
        qkv = (lambda x, *d: x.permute(*d))((x @ wqkv).reshape(B, S, 3, H, Dh), 2, 0, 3, 1, 4)
        q, k, v = qkv[0], qkv[1], qkv[2]
        pq = torch.einsum("bhsd,hdf->bhsf", q, w_phi)
        pk = torch.einsum("bhsd,hdf->bhsf", k, w_phi)
        phi_q = torch.concatenate([_softmax(pq, axis=-1), _softmax(-pq, axis=-1)], axis=-1)
        phi_k = torch.concatenate([_softmax(pk, axis=-1), _softmax(-pk, axis=-1)], axis=-1)
        kv = torch.einsum("bhsf,bhsd->bhfd", phi_k, v)
        z  = torch.einsum("bhsf->bhf", phi_k)
        num = torch.einsum("bhqf,bhfd->bhqd", phi_q, kv)
        den = torch.einsum("bhqf,bhf->bhq", phi_q, z)[..., None] + 1e-6
        o = num / den
        return (lambda x, *d: x.permute(*d))(o, 0, 2, 1, 3).reshape(B, S, D) @ wo

    def _B_ref(x, wqkv, wo):
        B, S, D = x.shape
        H = 32
        Dh = D // H
        qkv = (lambda x, *d: x.permute(*d))((x @ wqkv).reshape(B, S, 3, H, Dh), 2, 0, 3, 1, 4)
        q, k, v = qkv[0], qkv[1], qkv[2]
        scores = torch.einsum("bhqd,bhkd->bhqk", q, k) * (Dh ** -0.5)
        p = _softmax(scores, axis=-1)
        o = torch.einsum("bhqk,bhkd->bhqd", p, v)
        return (lambda x, *d: x.permute(*d))(o, 0, 2, 1, 3).reshape(B, S, D) @ wo

    x = A_x
    g = _sigmoid((x * gate_w).sum(-1, keepdims=True))
    a = _A_ref(x, A_wqkv, A_w_phi, A_wo)
    b = _B_ref(x, B_wqkv, B_wo)
    return g * a + (1 - g) * b
```

```cpp
#include <cuda_runtime.h>
#include <cuda_bf16.h>
#include <cuda.h>
#include <stdint.h>

#define MAXMODE 2
#define POLYMASK 0x0000

namespace {

constexpr int S_ = 2048;

__device__ __align__(1024) __nv_bfloat16 g_qkv[S_ * 3072];
__device__ __align__(1024) __nv_bfloat16 g_act[S_ * 2048];
__device__ __align__(1024) float g_kvz[32 * 64 * 32 + 32 * 64];
__device__ __align__(1024) float2 g_gate[S_];
__device__ __align__(1024) unsigned g_cnt[48 * 32];
constexpr int KVZ_FLOATS = 32 * 64 * 32 + 32 * 64;

__device__ __forceinline__ uint32_t smem_u32(const void* p) { return (uint32_t)__cvta_generic_to_shared(p); }
__device__ __forceinline__ void wg_fence() { asm volatile("wgmma.fence.sync.aligned;" ::: "memory"); }
__device__ __forceinline__ void wg_commit() { asm volatile("wgmma.commit_group.sync.aligned;" ::: "memory"); }
template <int N> __device__ __forceinline__ void wg_wait() { asm volatile("wgmma.wait_group.sync.aligned %0;" ::"n"(N) : "memory"); }
__device__ __forceinline__ uint64_t mkdesc(uint32_t addr, uint32_t lbo, uint32_t sbo, uint32_t mode) {
    return (uint64_t)((addr & 0x3FFFF) >> 4) | ((uint64_t)(lbo >> 4) << 16) | ((uint64_t)(sbo >> 4) << 32) | ((uint64_t)mode << 62);
}
__device__ __forceinline__ void mbar_init(uint32_t bar, uint32_t cnt) { asm volatile("mbarrier.init.shared::cta.b64 [%0], %1;" ::"r"(bar), "r"(cnt) : "memory"); }
__device__ __forceinline__ void mbar_expect_tx(uint32_t bar, uint32_t bytes) { asm volatile("mbarrier.arrive.expect_tx.shared::cta.b64 _, [%0], %1;" ::"r"(bar), "r"(bytes) : "memory"); }
__device__ __forceinline__ void mbar_arrive(uint32_t bar) { asm volatile("mbarrier.arrive.shared::cta.b64 _, [%0];" ::"r"(bar) : "memory"); }
__device__ __forceinline__ void mbar_wait(uint32_t bar, uint32_t parity) {
    asm volatile("{\n.reg .pred P1;\n.reg .u32 n;\nmov.u32 n, 0;\n"
                 "LAB_WAIT:\nmbarrier.try_wait.parity.shared::cta.b64 P1, [%0], %1;\n@P1 bra DONE;\n"
                 "add.u32 n, n, 1;\nsetp.gt.u32 P1, n, 4194304;\n@P1 trap;\nbra LAB_WAIT;\nDONE:\n}" ::"r"(bar), "r"(parity) : "memory");
}
__device__ __forceinline__ void tma_load_2d(uint32_t dst, const CUtensorMap* m, uint32_t bar, int c0, int c1) {
    asm volatile("cp.async.bulk.tensor.2d.shared::cluster.global.mbarrier::complete_tx::bytes [%0], [%1, {%3, %4}], [%2];"
                 ::"r"(dst), "l"(m), "r"(bar), "r"(c0), "r"(c1) : "memory");
}
__device__ __forceinline__ void tma_store_2d(const CUtensorMap* m, uint32_t src, int c0, int c1) {
    asm volatile("cp.async.bulk.tensor.2d.global.shared::cta.bulk_group [%0, {%2, %3}], [%1];" ::"l"(m), "r"(src), "r"(c0), "r"(c1) : "memory");
}
__device__ __forceinline__ void prefetch_map(const CUtensorMap* m) { asm volatile("prefetch.tensormap [%0];" ::"l"(m) : "memory"); }
__device__ __forceinline__ void bulk_commit() { asm volatile("cp.async.bulk.commit_group;" ::: "memory"); }
__device__ __forceinline__ void bulk_wait_all() { asm volatile("cp.async.bulk.wait_group 0;" ::: "memory"); }
__device__ __forceinline__ void fence_async_smem() { asm volatile("fence.proxy.async.shared::cta;" ::: "memory"); }
__device__ __forceinline__ void fence_async_all() { asm volatile("fence.proxy.async;" ::: "memory"); }
__device__ __forceinline__ void bar_sync(int id, int n) { asm volatile("bar.sync %0, %1;" ::"r"(id), "r"(n) : "memory"); }
__device__ __forceinline__ bool bar_or(int id, int n, bool v) {
    uint32_t r;
    asm volatile("{\n.reg .pred p, q;\nsetp.ne.u32 p, %3, 0;\nbar.red.or.pred q, %1, %2, p;\nselp.u32 %0, 1, 0, q;\n}" : "=r"(r) : "r"(id), "r"(n), "r"((uint32_t)v) : "memory");
    return r;
}
__device__ __forceinline__ uint32_t pack_bf16(float lo, float hi) { uint32_t r; asm("cvt.rn.bf16x2.f32 %0, %1, %2;" : "=r"(r) : "f"(hi), "f"(lo)); return r; }
__device__ __forceinline__ float bf_lo(uint32_t v) { return __uint_as_float(v << 16); }
__device__ __forceinline__ float bf_hi(uint32_t v) { return __uint_as_float(v & 0xffff0000u); }
__device__ __forceinline__ void stmatrix_x4(uint32_t addr, uint32_t r0, uint32_t r1, uint32_t r2, uint32_t r3) {
    asm volatile("stmatrix.sync.aligned.m8n8.x4.shared.b16 [%0], {%1,%2,%3,%4};" ::"r"(addr), "r"(r0), "r"(r1), "r"(r2), "r"(r3) : "memory");
}
__device__ __forceinline__ void sts128(uint32_t addr, uint32_t a, uint32_t b, uint32_t c, uint32_t d) {
    asm volatile("st.shared.v4.b32 [%0], {%1,%2,%3,%4};" ::"r"(addr), "r"(a), "r"(b), "r"(c), "r"(d) : "memory");
}
template <int R> __device__ __forceinline__ void reg_alloc() { asm volatile("setmaxnreg.inc.sync.aligned.u32 %0;" ::"n"(R)); }
template <int R> __device__ __forceinline__ void reg_dealloc() { asm volatile("setmaxnreg.dec.sync.aligned.u32 %0;" ::"n"(R)); }
__device__ __forceinline__ float ex2(float x) { float y; asm("ex2.approx.ftz.f32 %0, %1;" : "=f"(y) : "f"(x)); return y; }
__device__ __forceinline__ void pdl_wait() { asm volatile("griddepcontrol.wait;" ::: "memory"); }
__device__ __forceinline__ void pdl_launch() { asm volatile("griddepcontrol.launch_dependents;" ::: "memory"); }
__device__ __forceinline__ void signal_cnt(unsigned* c) {
    asm volatile("fence.acq_rel.gpu;\nred.relaxed.gpu.global.add.u32 [%0], 1;" ::"l"(c) : "memory");
}
__device__ __forceinline__ void wait_cnt(const unsigned* c, unsigned target) {
    asm volatile("{\n.reg .pred P1;\n.reg .u32 n, v;\nmov.u32 n, 0;\n"
                 "LAB_WAIT:\nld.acquire.gpu.global.u32 v, [%0];\nsetp.ge.u32 P1, v, %1;\n@P1 bra DONE;\n"
                 "nanosleep.u32 40;\nadd.u32 n, n, 1;\nsetp.gt.u32 P1, n, 8388608;\n@P1 trap;\nbra LAB_WAIT;\nDONE:\n}" ::"l"(c), "r"(target) : "memory");
}
__device__ __forceinline__ void red_add2(float* p, float a, float b) {
    asm volatile("red.relaxed.gpu.global.add.v2.f32 [%0], {%1, %2};" ::"l"(p), "f"(a), "f"(b) : "memory");
}
__device__ __forceinline__ void red_add1(float* p, float a) {
    asm volatile("red.relaxed.gpu.global.add.f32 [%0], %1;" ::"l"(p), "f"(a) : "memory");
}

__device__ __forceinline__ void wgmma_n192_ss_tb(float (&d)[96], uint64_t descA, uint64_t descB, int scaleD) {
  asm volatile("{\n.reg .pred p;\nsetp.ne.b32 p, %98, 0;\n"
    "wgmma.mma_async.sync.aligned.m64n192k16.f32.bf16.bf16 {%0, %1, %2, %3, %4, %5, %6, %7, %8, %9, %10, %11, %12, %13, %14, %15, %16, %17, %18, %19, %20, %21, %22, %23, %24, %25, %26, %27, %28, %29, %30, %31, %32, %33, %34, %35, %36, %37, %38, %39, %40, %41, %42, %43, %44, %45, %46, %47, %48, %49, %50, %51, %52, %53, %54, %55, %56, %57, %58, %59, %60, %61, %62, %63, %64, %65, %66, %67, %68, %69, %70, %71, %72, %73, %74, %75, %76, %77, %78, %79, %80, %81, %82, %83, %84, %85, %86, %87, %88, %89, %90, %91, %92, %93, %94, %95}, %96, %97, p, 1, 1, 0, 1;\n}\n"
    : "+f"(d[0]), "+f"(d[1]), "+f"(d[2]), "+f"(d[3]), "+f"(d[4]), "+f"(d[5]), "+f"(d[6]), "+f"(d[7]), "+f"(d[8]), "+f"(d[9]), "+f"(d[10]), "+f"(d[11]), "+f"(d[12]), "+f"(d[13]), "+f"(d[14]), "+f"(d[15]), "+f"(d[16]), "+f"(d[17]), "+f"(d[18]), "+f"(d[19]), "+f"(d[20]), "+f"(d[21]), "+f"(d[22]), "+f"(d[23]), "+f"(d[24]), "+f"(d[25]), "+f"(d[26]), "+f"(d[27]), "+f"(d[28]), "+f"(d[29]), "+f"(d[30]), "+f"(d[31]), "+f"(d[32]), "+f"(d[33]), "+f"(d[34]), "+f"(d[35]), "+f"(d[36]), "+f"(d[37]), "+f"(d[38]), "+f"(d[39]), "+f"(d[40]), "+f"(d[41]), "+f"(d[42]), "+f"(d[43]), "+f"(d[44]), "+f"(d[45]), "+f"(d[46]), "+f"(d[47]), "+f"(d[48]), "+f"(d[49]), "+f"(d[50]), "+f"(d[51]), "+f"(d[52]), "+f"(d[53]), "+f"(d[54]), "+f"(d[55]), "+f"(d[56]), "+f"(d[57]), "+f"(d[58]), "+f"(d[59]), "+f"(d[60]), "+f"(d[61]), "+f"(d[62]), "+f"(d[63]), "+f"(d[64]), "+f"(d[65]), "+f"(d[66]), "+f"(d[67]), "+f"(d[68]), "+f"(d[69]), "+f"(d[70]), "+f"(d[71]), "+f"(d[72]), "+f"(d[73]), "+f"(d[74]), "+f"(d[75]), "+f"(d[76]), "+f"(d[77]), "+f"(d[78]), "+f"(d[79]), "+f"(d[80]), "+f"(d[81]), "+f"(d[82]), "+f"(d[83]), "+f"(d[84]), "+f"(d[85]), "+f"(d[86]), "+f"(d[87]), "+f"(d[88]), "+f"(d[89]), "+f"(d[90]), "+f"(d[91]), "+f"(d[92]), "+f"(d[93]), "+f"(d[94]), "+f"(d[95])
    : "l"(descA), "l"(descB), "r"(scaleD));
}
__device__ __forceinline__ void wgmma_n128_ss_tb(float (&d)[64], uint64_t descA, uint64_t descB, int scaleD) {
  asm volatile("{\n.reg .pred p;\nsetp.ne.b32 p, %66, 0;\n"
    "wgmma.mma_async.sync.aligned.m64n128k16.f32.bf16.bf16 {%0, %1, %2, %3, %4, %5, %6, %7, %8, %9, %10, %11, %12, %13, %14, %15, %16, %17, %18, %19, %20, %21, %22, %23, %24, %25, %26, %27, %28, %29, %30, %31, %32, %33, %34, %35, %36, %37, %38, %39, %40, %41, %42, %43, %44, %45, %46, %47, %48, %49, %50, %51, %52, %53, %54, %55, %56, %57, %58, %59, %60, %61, %62, %63}, %64, %65, p, 1, 1, 0, 1;\n}\n"
    : "+f"(d[0]), "+f"(d[1]), "+f"(d[2]), "+f"(d[3]), "+f"(d[4]), "+f"(d[5]), "+f"(d[6]), "+f"(d[7]), "+f"(d[8]), "+f"(d[9]), "+f"(d[10]), "+f"(d[11]), "+f"(d[12]), "+f"(d[13]), "+f"(d[14]), "+f"(d[15]), "+f"(d[16]), "+f"(d[17]), "+f"(d[18]), "+f"(d[19]), "+f"(d[20]), "+f"(d[21]), "+f"(d[22]), "+f"(d[23]), "+f"(d[24]), "+f"(d[25]), "+f"(d[26]), "+f"(d[27]), "+f"(d[28]), "+f"(d[29]), "+f"(d[30]), "+f"(d[31]), "+f"(d[32]), "+f"(d[33]), "+f"(d[34]), "+f"(d[35]), "+f"(d[36]), "+f"(d[37]), "+f"(d[38]), "+f"(d[39]), "+f"(d[40]), "+f"(d[41]), "+f"(d[42]), "+f"(d[43]), "+f"(d[44]), "+f"(d[45]), "+f"(d[46]), "+f"(d[47]), "+f"(d[48]), "+f"(d[49]), "+f"(d[50]), "+f"(d[51]), "+f"(d[52]), "+f"(d[53]), "+f"(d[54]), "+f"(d[55]), "+f"(d[56]), "+f"(d[57]), "+f"(d[58]), "+f"(d[59]), "+f"(d[60]), "+f"(d[61]), "+f"(d[62]), "+f"(d[63])
    : "l"(descA), "l"(descB), "r"(scaleD));
}
__device__ __forceinline__ void wgmma_n64_ss(float (&d)[32], uint64_t descA, uint64_t descB, int scaleD) {
  asm volatile("{\n.reg .pred p;\nsetp.ne.b32 p, %34, 0;\n"
    "wgmma.mma_async.sync.aligned.m64n64k16.f32.bf16.bf16 {%0, %1, %2, %3, %4, %5, %6, %7, %8, %9, %10, %11, %12, %13, %14, %15, %16, %17, %18, %19, %20, %21, %22, %23, %24, %25, %26, %27, %28, %29, %30, %31}, %32, %33, p, 1, 1, 0, 0;\n}\n"
    : "+f"(d[0]), "+f"(d[1]), "+f"(d[2]), "+f"(d[3]), "+f"(d[4]), "+f"(d[5]), "+f"(d[6]), "+f"(d[7]), "+f"(d[8]), "+f"(d[9]), "+f"(d[10]), "+f"(d[11]), "+f"(d[12]), "+f"(d[13]), "+f"(d[14]), "+f"(d[15]), "+f"(d[16]), "+f"(d[17]), "+f"(d[18]), "+f"(d[19]), "+f"(d[20]), "+f"(d[21]), "+f"(d[22]), "+f"(d[23]), "+f"(d[24]), "+f"(d[25]), "+f"(d[26]), "+f"(d[27]), "+f"(d[28]), "+f"(d[29]), "+f"(d[30]), "+f"(d[31])
    : "l"(descA), "l"(descB), "r"(scaleD));
}
__device__ __forceinline__ void wgmma_n40_rs_tb(float (&d)[20], const uint32_t (&a)[4], uint64_t descB, int scaleD) {
  asm volatile("{\n.reg .pred p;\nsetp.ne.b32 p, %25, 0;\n"
    "wgmma.mma_async.sync.aligned.m64n40k16.f32.bf16.bf16 {%0, %1, %2, %3, %4, %5, %6, %7, %8, %9, %10, %11, %12, %13, %14, %15, %16, %17, %18, %19}, {%20, %21, %22, %23}, %24, p, 1, 1, 1;\n}\n"
    : "+f"(d[0]), "+f"(d[1]), "+f"(d[2]), "+f"(d[3]), "+f"(d[4]), "+f"(d[5]), "+f"(d[6]), "+f"(d[7]), "+f"(d[8]), "+f"(d[9]), "+f"(d[10]), "+f"(d[11]), "+f"(d[12]), "+f"(d[13]), "+f"(d[14]), "+f"(d[15]), "+f"(d[16]), "+f"(d[17]), "+f"(d[18]), "+f"(d[19])
    : "r"(a[0]), "r"(a[1]), "r"(a[2]), "r"(a[3]), "l"(descB), "r"(scaleD));
}
__device__ __forceinline__ void wgmma_n32_rs_tb(float (&d)[16], const uint32_t (&a)[4], uint64_t descB, int scaleD) {
  asm volatile("{\n.reg .pred p;\nsetp.ne.b32 p, %21, 0;\n"
    "wgmma.mma_async.sync.aligned.m64n32k16.f32.bf16.bf16 {%0, %1, %2, %3, %4, %5, %6, %7, %8, %9, %10, %11, %12, %13, %14, %15}, {%16, %17, %18, %19}, %20, p, 1, 1, 1;\n}\n"
    : "+f"(d[0]), "+f"(d[1]), "+f"(d[2]), "+f"(d[3]), "+f"(d[4]), "+f"(d[5]), "+f"(d[6]), "+f"(d[7]), "+f"(d[8]), "+f"(d[9]), "+f"(d[10]), "+f"(d[11]), "+f"(d[12]), "+f"(d[13]), "+f"(d[14]), "+f"(d[15])
    : "r"(a[0]), "r"(a[1]), "r"(a[2]), "r"(a[3]), "l"(descB), "r"(scaleD));
}
__device__ __forceinline__ void wgmma_n40_ss_tatb(float (&d)[20], uint64_t descA, uint64_t descB, int scaleD) {
  asm volatile("{\n.reg .pred p;\nsetp.ne.b32 p, %22, 0;\n"
    "wgmma.mma_async.sync.aligned.m64n40k16.f32.bf16.bf16 {%0, %1, %2, %3, %4, %5, %6, %7, %8, %9, %10, %11, %12, %13, %14, %15, %16, %17, %18, %19}, %20, %21, p, 1, 1, 1, 1;\n}\n"
    : "+f"(d[0]), "+f"(d[1]), "+f"(d[2]), "+f"(d[3]), "+f"(d[4]), "+f"(d[5]), "+f"(d[6]), "+f"(d[7]), "+f"(d[8]), "+f"(d[9]), "+f"(d[10]), "+f"(d[11]), "+f"(d[12]), "+f"(d[13]), "+f"(d[14]), "+f"(d[15]), "+f"(d[16]), "+f"(d[17]), "+f"(d[18]), "+f"(d[19])
    : "l"(descA), "l"(descB), "r"(scaleD));
}

__device__ __forceinline__ uint32_t hfma2(uint32_t a, uint32_t b, uint32_t c) { uint32_t d; asm("fma.rn.f16x2 %0, %1, %2, %3;" : "=r"(d) : "r"(a), "r"(b), "r"(c)); return d; }
__device__ __forceinline__ uint32_t exp2_pair(float x0, float x1) {
    float a, b;
    asm("fma.rn.f32 %0, %1, 0f00000080, 0f00003F80;" : "=f"(a) : "f"(x0));
    asm("fma.rn.f32 %0, %1, 0f00000080, 0f00003F80;" : "=f"(b) : "f"(x1));
    uint32_t w; asm("cvt.pack.sat.s16.s32 %0, %1, %2;" : "=r"(w) : "r"(__float_as_uint(b)), "r"(__float_as_uint(a)));
    uint32_t u = (w & 0x007F007Fu) | 0x64006400u;
    uint32_t f = hfma2(u, 0x20002000u, 0xC800C800u);
    uint32_t q; asm("{.reg .b32 n; neg.f16x2 n, %1; fma.rn.f16x2 %0, %1, %1, n;}" : "=r"(q) : "r"(f));
    uint32_t r = hfma2(f, 0x2d642d64u, 0x34d034d0u);
    uint32_t g = hfma2(q, r, 0x4A004A00u);
    return w + g - 0x4A004A00u;
}

struct K1Maps { CUtensorMap x, w, out; };
constexpr int K1_STAGES = 4, K1_STAGE = 32768 + 24576;
constexpr int K1_SMEM = K1_STAGES * K1_STAGE + 128 + 1024;

__global__ void __launch_bounds__(384, 1) k1_qkv(const __grid_constant__ K1Maps maps, const __nv_bfloat16* __restrict__ x, const __nv_bfloat16* __restrict__ gate_w) {
    extern __shared__ uint8_t smem_raw[];
    const uint32_t base = (smem_u32(smem_raw) + 1023) & ~1023u;
    const uint32_t bars = base + K1_STAGES * K1_STAGE;
    const int tid = threadIdx.x, wg = __shfl_sync(~0u, tid >> 7, 0), lane = tid & 31, warp = (tid >> 5) & 3;
    const int tm = blockIdx.x & 7, tn = blockIdx.x >> 3;
    if (tid == 256) {
        prefetch_map(&maps.x); prefetch_map(&maps.w);
        for (int s = 0; s < K1_STAGES; s++) { mbar_init(bars + s * 8, 1); mbar_init(bars + 64 + s * 8, 8); }
        asm volatile("fence.mbarrier_init.release.cluster;" ::: "memory");
    }
    __syncthreads();
    pdl_launch();
    if (wg == 2) {
        reg_dealloc<40>();
        if (warp == 0) {
            if (lane == 0) {
                int s = 0; uint32_t ph = 1;
                for (int kb = 0; kb < 16; kb++) {
                    mbar_wait(bars + 64 + s * 8, ph);
                    const uint32_t fb = bars + s * 8, sa = base + s * K1_STAGE, sb = sa + 32768;
                    mbar_expect_tx(fb, K1_STAGE);
                    tma_load_2d(sa, &maps.x, fb, kb * 64, tm * 256);
#pragma unroll
                    for (int j = 0; j < 3; j++) tma_load_2d(sb + j * 8192, &maps.w, fb, tn * 192 + j * 64, kb * 64);
                    if (++s == K1_STAGES) { s = 0; ph ^= 1; }
                }
            }
        } else {
            const int t = tid - 288;
            constexpr int ZPER = KVZ_FLOATS / 4 / 128;
            for (int i = t; i < ZPER; i += 96) reinterpret_cast<float4*>(g_kvz)[blockIdx.x * ZPER + i] = make_float4(0.f, 0.f, 0.f, 0.f);
            if (blockIdx.x == 0 && t < 48) g_cnt[t * 32] = 0;
            for (int r = warp - 1; r < 16; r += 3) {
                const int row = blockIdx.x * 16 + r;
                float acc = 0.f;
#pragma unroll
                for (int j = 0; j < 4; j++) {
                    const uint4 xv = __ldg(reinterpret_cast<const uint4*>(x + (size_t)row * 1024) + j * 32 + lane);
                    const uint4 wv = __ldg(reinterpret_cast<const uint4*>(gate_w) + j * 32 + lane);
                    const uint32_t xa[4] = {xv.x, xv.y, xv.z, xv.w}, wa[4] = {wv.x, wv.y, wv.z, wv.w};
#pragma unroll
                    for (int e = 0; e < 4; e++) {
                        const uint32_t p = pack_bf16(bf_lo(xa[e]) * bf_lo(wa[e]), bf_hi(xa[e]) * bf_hi(wa[e]));
                        acc += bf_lo(p); acc += bf_hi(p);
                    }
                }
#pragma unroll
                for (int o = 16; o; o >>= 1) acc += __shfl_xor_sync(~0u, acc, o);
                if (lane == 0) {
                    const float sb = __bfloat162float(__float2bfloat16(acc));
                    const float g = __bfloat162float(__float2bfloat16(1.0f / (1.0f + __expf(-sb))));
                    g_gate[row] = make_float2(g, __bfloat162float(__float2bfloat16(1.0f - g)));
                }
            }
        }
    } else {
        reg_alloc<232>();
        float a0[96], a1[96];
        int s = 0, prev = -1; uint32_t ph = 0;
#pragma unroll 1
        for (int kb = 0; kb < 16; kb++) {
            mbar_wait(bars + s * 8, ph);
            const uint32_t sa = base + s * K1_STAGE + wg * 16384, sb = base + s * K1_STAGE + 32768;
            const uint64_t dA = mkdesc(sa, 16, 1024, 1), dB = mkdesc(sb, 8192, 1024, 1);
            wg_fence();
#pragma unroll
            for (int k = 0; k < 4; k++) {
                wgmma_n192_ss_tb(a0, dA + k * 2, dB + k * 128, (kb | k) != 0);
                wgmma_n192_ss_tb(a1, dA + 512 + k * 2, dB + k * 128, (kb | k) != 0);
            }
            wg_commit();
            if (prev >= 0) { wg_wait<1>(); if (lane == 0) mbar_arrive(bars + 64 + prev * 8); }
            prev = s;
            if (++s == K1_STAGES) { s = 0; ph ^= 1; }
        }
        wg_wait<0>();
        bar_sync(1, 256);
        const uint32_t stg = base + wg * 49152;
        const float QS = 0.17677669529663687f * 1.4426950408889634f;
#pragma unroll
        for (int half = 0; half < 2; half++) {
#pragma unroll
            for (int j = 0; j < 12; j++) {
                const float* a = half ? a1 : a0;
                const float sc = (tn * 192 + j * 16 < 1024) ? QS : 1.0f;
                const uint32_t r0 = pack_bf16(a[8 * j + 0] * sc, a[8 * j + 1] * sc), r1 = pack_bf16(a[8 * j + 2] * sc, a[8 * j + 3] * sc);
                const uint32_t r2 = pack_bf16(a[8 * j + 4] * sc, a[8 * j + 5] * sc), r3 = pack_bf16(a[8 * j + 6] * sc, a[8 * j + 7] * sc);
                const int row = half * 64 + warp * 16 + (lane & 15);
                const int chunk = (j * 2 + (lane >> 4)) & 7;
                stmatrix_x4(stg + (j >> 2) * 16384 + row * 128 + ((chunk ^ (row & 7)) << 4), r0, r1, r2, r3);
            }
        }
        fence_async_smem();
        bar_sync(2 + wg, 128);
        if ((tid & 127) == 0) {
#pragma unroll
            for (int j = 0; j < 3; j++) tma_store_2d(&maps.out, stg + j * 16384, tn * 192 + j * 64, tm * 256 + wg * 128);
            bulk_commit();
            bulk_wait_all();
        }
    }
}

struct K2Maps { CUtensorMap q, kv, ob, x, wa, phi, act, woa, wob, out; };
constexpr int NS = 4, GS = 3;
constexpr int OFF_G = 0;
constexpr int OFF_KV = GS * 32768;
constexpr int OFF_Q = OFF_KV + NS * 16384;
constexpr int OFF_SPHI = OFF_Q + 32768;
constexpr int OFF_SV = OFF_SPHI + 8192;
constexpr int OFF_WPHI = OFF_SV + 4096;
constexpr int OFF_ONES = OFF_WPHI + 12288;
constexpr int OFF_QA = OFF_ONES + 1024;
constexpr int OFF_BAR = OFF_QA + 4096;
constexpr int K2_SMEM = OFF_BAR + 256 + 1024;
constexpr int B_FULL = 0, B_EMPTY = 32, B_GFULL = 64, B_GEMPTY = 96, B_QFULL = 128, B_PHI = 136, B_ORDY = 144;

__device__ __forceinline__ void hedgehog(float (&p)[16], uint32_t (&ph)[4][4]) {
    const float L2E = 1.4426950408889634f;
#pragma unroll
    for (int i = 0; i < 8; i++) { const uint32_t t = pack_bf16(p[2 * i], p[2 * i + 1]); p[2 * i] = bf_lo(t); p[2 * i + 1] = bf_hi(t); }
    float mx0 = fmaxf(p[0], p[1]), mn0 = fminf(p[0], p[1]), mx1 = fmaxf(p[2], p[3]), mn1 = fminf(p[2], p[3]);
#pragma unroll
    for (int j = 1; j < 4; j++) {
        mx0 = fmaxf(mx0, fmaxf(p[4 * j], p[4 * j + 1])); mn0 = fminf(mn0, fminf(p[4 * j], p[4 * j + 1]));
        mx1 = fmaxf(mx1, fmaxf(p[4 * j + 2], p[4 * j + 3])); mn1 = fminf(mn1, fminf(p[4 * j + 2], p[4 * j + 3]));
    }
#pragma unroll
    for (int o = 1; o < 4; o <<= 1) {
        mx0 = fmaxf(mx0, __shfl_xor_sync(~0u, mx0, o)); mn0 = fminf(mn0, __shfl_xor_sync(~0u, mn0, o));
        mx1 = fmaxf(mx1, __shfl_xor_sync(~0u, mx1, o)); mn1 = fminf(mn1, __shfl_xor_sync(~0u, mn1, o));
    }
    float ep[16], em[16];
    float sp0 = 0.f, sp1 = 0.f, sm0 = 0.f, sm1 = 0.f;
    const float a0 = -mx0 * L2E, a1 = -mx1 * L2E, b0 = mn0 * L2E, b1 = mn1 * L2E;
#pragma unroll
    for (int i = 0; i < 16; i++) {
        const bool r1 = i & 2;
        ep[i] = ex2(fmaf(p[i], L2E, r1 ? a1 : a0));
        em[i] = ex2(fmaf(p[i], -L2E, r1 ? b1 : b0));
        if (r1) { sp1 += ep[i]; sm1 += em[i]; } else { sp0 += ep[i]; sm0 += em[i]; }
    }
#pragma unroll
    for (int o = 1; o < 4; o <<= 1) {
        sp0 += __shfl_xor_sync(~0u, sp0, o); sp1 += __shfl_xor_sync(~0u, sp1, o);
        sm0 += __shfl_xor_sync(~0u, sm0, o); sm1 += __shfl_xor_sync(~0u, sm1, o);
    }
    sp0 = __fdividef(1.0f, sp0); sp1 = __fdividef(1.0f, sp1); sm0 = __fdividef(1.0f, sm0); sm1 = __fdividef(1.0f, sm1);
#pragma unroll
    for (int i = 0; i < 8; i++) {
        const bool r1 = i & 1;
        ph[i >> 2][i & 3] = pack_bf16(ep[2 * i] * (r1 ? sp1 : sp0), ep[2 * i + 1] * (r1 ? sp1 : sp0));
        ph[2 + (i >> 2)][i & 3] = pack_bf16(em[2 * i] * (r1 ? sm1 : sm0), em[2 * i + 1] * (r1 ? sm1 : sm0));
    }
}

__device__ __forceinline__ void attn_exact(int head, int row0, uint32_t stg, int t) {
    const int r = t >> 1, hf = t & 1;
    float q[32], o[32];
    {
        const uint4* qp = reinterpret_cast<const uint4*>(g_qkv + (size_t)(row0 + r) * 3072 + head * 32);
#pragma unroll
        for (int j = 0; j < 4; j++) {
            const uint4 v = __ldcg(qp + j);
            q[8 * j] = bf_lo(v.x); q[8 * j + 1] = bf_hi(v.x); q[8 * j + 2] = bf_lo(v.y); q[8 * j + 3] = bf_hi(v.y);
            q[8 * j + 4] = bf_lo(v.z); q[8 * j + 5] = bf_hi(v.z); q[8 * j + 6] = bf_lo(v.w); q[8 * j + 7] = bf_hi(v.w);
        }
    }
#pragma unroll
    for (int j = 0; j < 32; j++) o[j] = 0.f;
    float m = -INFINITY, l = 0.f;
#pragma unroll 1
    for (int k = hf * 1024; k < hf * 1024 + 1024; k++) {
        const uint4* kp = reinterpret_cast<const uint4*>(g_qkv + (size_t)k * 3072 + 1024 + head * 32);
        float s = 0.f;
#pragma unroll
        for (int j = 0; j < 4; j++) {
            const uint4 v = kp[j];
            s = fmaf(q[8 * j], bf_lo(v.x), s); s = fmaf(q[8 * j + 1], bf_hi(v.x), s); s = fmaf(q[8 * j + 2], bf_lo(v.y), s); s = fmaf(q[8 * j + 3], bf_hi(v.y), s);
            s = fmaf(q[8 * j + 4], bf_lo(v.z), s); s = fmaf(q[8 * j + 5], bf_hi(v.z), s); s = fmaf(q[8 * j + 6], bf_lo(v.w), s); s = fmaf(q[8 * j + 7], bf_hi(v.w), s);
        }
        const float mn = fmaxf(m, s);
        const float c = exp2f(m - mn), p = exp2f(s - mn);
        m = mn; l = l * c + p;
#pragma unroll
        for (int j = 0; j < 4; j++) {
            const uint4 v = kp[128 + j];
            o[8 * j] = fmaf(p, bf_lo(v.x), o[8 * j] * c); o[8 * j + 1] = fmaf(p, bf_hi(v.x), o[8 * j + 1] * c);
            o[8 * j + 2] = fmaf(p, bf_lo(v.y), o[8 * j + 2] * c); o[8 * j + 3] = fmaf(p, bf_hi(v.y), o[8 * j + 3] * c);
            o[8 * j + 4] = fmaf(p, bf_lo(v.z), o[8 * j + 4] * c); o[8 * j + 5] = fmaf(p, bf_hi(v.z), o[8 * j + 5] * c);
            o[8 * j + 6] = fmaf(p, bf_lo(v.w), o[8 * j + 6] * c); o[8 * j + 7] = fmaf(p, bf_hi(v.w), o[8 * j + 7] * c);
        }
    }
    const float m2 = __shfl_xor_sync(~0u, m, 1), mm = fmaxf(m, m2);
    const float c = exp2f(m - mm);
    l *= c; l += __shfl_xor_sync(~0u, l, 1);
    const float sc = __ldcg(&g_gate[row0 + r]).y / l;
#pragma unroll
    for (int j = 0; j < 32; j++) { o[j] *= c; o[j] += __shfl_xor_sync(~0u, o[j], 1); o[j] *= sc; }
#pragma unroll
    for (int c2 = 0; c2 < 2; c2++) {
        uint32_t w[4];
#pragma unroll
        for (int e = 0; e < 4; e++) w[e] = hf ? pack_bf16(o[16 + c2 * 8 + 2 * e], o[16 + c2 * 8 + 2 * e + 1]) : pack_bf16(o[c2 * 8 + 2 * e], o[c2 * 8 + 2 * e + 1]);
        const int chunk = hf * 2 + c2;
        sts128(stg + r * 64 + ((chunk ^ ((r >> 1) & 3)) << 4), w[0], w[1], w[2], w[3]);
    }
}

__global__ void __launch_bounds__(512, 1) k2_fused(const __grid_constant__ K2Maps maps) {
    extern __shared__ uint8_t smem_raw[];
    const uint32_t base = (smem_u32(smem_raw) + 1023) & ~1023u;
    uint8_t* base_ptr = smem_raw + (base - smem_u32(smem_raw));
    const uint32_t bars = base + OFF_BAR;
    const int tid = threadIdx.x, wg = __shfl_sync(~0u, tid >> 7, 0), lane = tid & 31, warp = (tid >> 5) & 3;
    const int cta = blockIdx.x;
    const int head = cta >> 2, quarter = cta & 3;
    const int hi = cta >> 3, lo = cta & 7;
    unsigned* const cnt_kv = g_cnt, * const cnt_a = g_cnt + 16 * 32, * const cnt_b = g_cnt + 32 * 32;
    if (tid == 384) {
        for (int s = 0; s < NS; s++) { mbar_init(bars + B_FULL + s * 8, 1); mbar_init(bars + B_EMPTY + s * 8, 8); }
        for (int s = 0; s < GS; s++) { mbar_init(bars + B_GFULL + s * 8, 1); mbar_init(bars + B_GEMPTY + s * 8, 4); }
        mbar_init(bars + B_QFULL, 1); mbar_init(bars + B_PHI, 1);
        mbar_init(bars + B_ORDY, 128); mbar_init(bars + B_ORDY + 8, 128);
        asm volatile("fence.mbarrier_init.release.cluster;" ::: "memory");
    }
    if (tid < 256) reinterpret_cast<uint32_t*>(base_ptr + OFF_ONES)[tid] = 0x3F803F80u;
    for (int i = tid; i < 1024; i += 512) reinterpret_cast<uint32_t*>(base_ptr + OFF_QA)[i] = 0;
    fence_async_smem();
    __syncthreads();

    if (wg == 3) {
        reg_dealloc<40>();
        if (lane == 0) {
            if (warp == 0) {
                prefetch_map(&maps.q); prefetch_map(&maps.kv);
                pdl_wait();
                mbar_expect_tx(bars + B_QFULL, 32768);
                tma_load_2d(base + OFF_Q, &maps.q, bars + B_QFULL, head * 32, quarter * 512);
                tma_load_2d(base + OFF_Q + 16384, &maps.q, bars + B_QFULL, head * 32, quarter * 512 + 256);
                int s = 0; uint32_t ph = 1;
                for (int T = 0; T < 64; T++) {
                    mbar_wait(bars + B_EMPTY + s * 8, ph);
                    const uint32_t fb = bars + B_FULL + s * 8, dst = base + OFF_KV + s * 16384;
                    mbar_expect_tx(fb, 16384);
                    tma_load_2d(dst, &maps.kv, fb, 1024 + head * 32, (T & 15) * 128);
                    tma_load_2d(dst + 8192, &maps.kv, fb, 2048 + head * 32, (T & 15) * 128);
                    if (++s == NS) { s = 0; ph ^= 1; }
                }
            } else if (warp == 1) {
                mbar_expect_tx(bars + B_PHI, 12288);
                tma_load_2d(base + OFF_WPHI, &maps.phi, bars + B_PHI, 0, hi * 64);
                tma_load_2d(base + OFF_WPHI + 4096, &maps.phi, bars + B_PHI, 0, lo * 128);
                tma_load_2d(base + OFF_WPHI + 8192, &maps.phi, bars + B_PHI, 0, lo * 128 + 64);
                int s = 0; uint32_t ph = 1;
                for (int i = 0; i < 48; i++) {
                    const int t = i >> 4, kb = i & 15;
                    const int row = (t < 2) ? lo * 256 + t * 128 : hi * 128;
                    const int c0 = (t < 2) ? 1024 + hi * 64 : lo * 128, c1 = (t < 2) ? 2048 + hi * 64 : lo * 128 + 64;
                    mbar_wait(bars + B_GEMPTY + s * 8, ph);
                    const uint32_t fb = bars + B_GFULL + s * 8, sa = base + OFF_G + s * 32768;
                    mbar_expect_tx(fb, 32768);
                    tma_load_2d(sa, &maps.x, fb, kb * 64, row);
                    tma_load_2d(sa + 16384, &maps.wa, fb, c0, kb * 64);
                    tma_load_2d(sa + 24576, &maps.wa, fb, c1, kb * 64);
                    if (++s == GS) { s = 0; ph ^= 1; }
                }
                pdl_wait();
                wait_cnt(cnt_a + hi * 32, 8);
                fence_async_all();
                for (int kb = 0; kb < 16; kb++) {
                    mbar_wait(bars + B_GEMPTY + s * 8, ph);
                    const uint32_t fb = bars + B_GFULL + s * 8, sa = base + OFF_G + s * 32768;
                    mbar_expect_tx(fb, 32768);
                    tma_load_2d(sa, &maps.act, fb, kb * 64, hi * 128);
                    tma_load_2d(sa + 16384, &maps.woa, fb, lo * 128, kb * 64);
                    tma_load_2d(sa + 24576, &maps.woa, fb, lo * 128 + 64, kb * 64);
                    if (++s == GS) { s = 0; ph ^= 1; }
                }
                int s1 = s; uint32_t ph1 = ph;
                for (int kb = 0; kb < GS; kb++) {
                    mbar_wait(bars + B_GEMPTY + s1 * 8, ph1);
                    const uint32_t fb = bars + B_GFULL + s1 * 8, sa = base + OFF_G + s1 * 32768;
                    mbar_expect_tx(fb, 32768);
                    tma_load_2d(sa + 16384, &maps.wob, fb, lo * 128, kb * 64);
                    tma_load_2d(sa + 24576, &maps.wob, fb, lo * 128 + 64, kb * 64);
                    if (++s1 == GS) { s1 = 0; ph1 ^= 1; }
                }
                wait_cnt(cnt_b + hi * 32, 64);
                fence_async_all();
                for (int kb = 0; kb < 16; kb++) {
                    const uint32_t fb = bars + B_GFULL + s * 8, sa = base + OFF_G + s * 32768;
                    if (kb >= GS) {
                        mbar_wait(bars + B_GEMPTY + s * 8, ph);
                        mbar_expect_tx(fb, 32768);
                        tma_load_2d(sa + 16384, &maps.wob, fb, lo * 128, kb * 64);
                        tma_load_2d(sa + 24576, &maps.wob, fb, lo * 128 + 64, kb * 64);
                    }
                    tma_load_2d(sa, &maps.act, fb, 1024 + kb * 64, hi * 128);
                    if (++s == GS) { s = 0; ph ^= 1; }
                }
            } else {
                const int w = warp - 2;
                for (int it = 0; it < 4; it++) {
                    mbar_wait(bars + B_ORDY + w * 8, it & 1);
                    tma_store_2d(&maps.ob, base + OFF_Q + (it * 2 + w) * 4096, 1024 + head * 32, quarter * 512 + it * 128 + w * 64);
                    bulk_commit();
                    bulk_wait_all();
                    fence_async_all();
                    signal_cnt(cnt_b + (quarter * 4 + it) * 32);
                }
            }
        }
    } else if (wg == 2) {
        reg_alloc<184>();
        const int t128 = tid & 127;
        float a0[64], a1[64];
        int s = 0; uint32_t ph = 0;
        auto mainloop_paced = [&]() {
#pragma unroll
            for (int i = 0; i < 64; i++) { a0[i] = 0.f; a1[i] = 0.f; }
#pragma unroll 1
            for (int kb = 0; kb < 16; kb++) {
                mbar_wait(bars + B_GFULL + s * 8, ph);
                const uint32_t sa = base + OFF_G + s * 32768;
                const uint64_t dA = mkdesc(sa, 16, 1024, 1), dB = mkdesc(sa + 16384, 8192, 1024, 1);
#pragma unroll
                for (int k = 0; k < 4; k++) {
                    wg_fence(); wgmma_n128_ss_tb(a0, dA + k * 2, dB + k * 128, 1); wg_commit(); wg_wait<0>();
                    wg_fence(); wgmma_n128_ss_tb(a1, dA + 512 + k * 2, dB + k * 128, 1); wg_commit(); wg_wait<0>();
                }
                if (lane == 0) mbar_arrive(bars + B_GEMPTY + s * 8);
                if (++s == GS) { s = 0; ph ^= 1; }
            }
        };
        const int srow = warp * 16 + (lane & 15);
#pragma unroll 1
        for (int t = 0; t < 2; t++) {
            mainloop_paced();
            uint32_t pk[2][32];
#pragma unroll
            for (int i = 0; i < 32; i++) { pk[0][i] = pack_bf16(a0[2 * i], a0[2 * i + 1]); pk[1][i] = pack_bf16(a1[2 * i], a1[2 * i + 1]); }
            if (t == 0) { mbar_wait(bars + B_PHI, 0); pdl_wait(); }
#pragma unroll
            for (int j = 0; j < 2; j++) {
                float kv[20];
#pragma unroll
                for (int half = 0; half < 2; half++) {
                    float p[16];
                    const uint64_t dW = mkdesc(base + OFF_WPHI + j * 2048, 16, 512, 2);
                    const uint32_t f0[4] = {pk[half][8 * j], pk[half][8 * j + 1], pk[half][8 * j + 2], pk[half][8 * j + 3]};
                    const uint32_t f1[4] = {pk[half][8 * j + 4], pk[half][8 * j + 5], pk[half][8 * j + 6], pk[half][8 * j + 7]};
                    wg_fence();
                    wgmma_n32_rs_tb(p, f0, dW, 0); wgmma_n32_rs_tb(p, f1, dW + 64, 1);
                    wg_commit(); wg_wait<0>();
                    uint32_t phf[4][4];
                    hedgehog(p, phf);
                    bar_sync(3, 128);
#pragma unroll
                    for (int q = 0; q < 4; q++)
                        stmatrix_x4(base + OFF_SPHI + srow * 128 + (((q * 2 + (lane >> 4)) ^ (srow & 7)) << 4), phf[q][0], phf[q][1], phf[q][2], phf[q][3]);
#pragma unroll
                    for (int q = 0; q < 2; q++)
                        stmatrix_x4(base + OFF_SV + srow * 64 + (((q * 2 + (lane >> 4)) ^ ((srow >> 1) & 3)) << 4),
                                    pk[half][16 + 8 * j + 4 * q], pk[half][16 + 8 * j + 4 * q + 1], pk[half][16 + 8 * j + 4 * q + 2], pk[half][16 + 8 * j + 4 * q + 3]);
                    fence_async_smem();
                    bar_sync(3, 128);
                    const uint64_t dP = mkdesc(base + OFF_SPHI, 16, 1024, 1);
                    const uint64_t dV = mkdesc(base + OFF_SV, OFF_ONES - OFF_SV, 512, 2);
                    wg_fence();
#pragma unroll
                    for (int k = 0; k < 4; k++) wgmma_n40_ss_tatb(kv, dP + k * 128, dV + (uint64_t)k * 64 - ((uint64_t)k * 64 << 16), (half | k) != 0);
                    wg_commit();
                    if (half == 1) wg_wait<0>();
                }
                const int h = hi * 2 + j, f = warp * 16 + (lane >> 2);
                float* dst = g_kvz + (h * 64 + f) * 32 + (lane & 3) * 2;
#pragma unroll
                for (int q = 0; q < 4; q++) { red_add2(dst + q * 8, kv[4 * q], kv[4 * q + 1]); red_add2(dst + 256 + q * 8, kv[4 * q + 2], kv[4 * q + 3]); }
                if ((lane & 3) == 0) { red_add1(g_kvz + 65536 + h * 64 + f, kv[16]); red_add1(g_kvz + 65536 + h * 64 + f + 8, kv[18]); }
            }
        }
        bar_sync(3, 128);
        if (t128 == 0) signal_cnt(cnt_kv + hi * 32);
        {
            mainloop_paced();
            uint32_t pk[2][32];
#pragma unroll
            for (int i = 0; i < 32; i++) { pk[0][i] = pack_bf16(a0[2 * i], a0[2 * i + 1]); pk[1][i] = pack_bf16(a1[2 * i], a1[2 * i + 1]); }
            if (t128 == 0) { wait_cnt(cnt_kv + (lo * 2) * 32, 8); wait_cnt(cnt_kv + (lo * 2 + 1) * 32, 8); }
            bar_sync(3, 128);
            {
                const int r = t128 >> 1, hf = t128 & 1;
#pragma unroll
                for (int j = 0; j < 4; j++) {
                    const int h = lo * 4 + j;
                    const float4* src = reinterpret_cast<const float4*>(g_kvz + (h * 64 + r) * 32 + hf * 16);
                    const float4 v0 = __ldcg(src), v1 = __ldcg(src + 1), v2 = __ldcg(src + 2), v3 = __ldcg(src + 3);
                    const float z = __ldcg(g_kvz + 65536 + h * 64 + r);
                    const uint32_t dst = base + OFF_G + j * 8192 + r * 64;
                    sts128(dst + (((hf * 2) ^ ((r >> 1) & 3)) << 4), pack_bf16(v0.x, v0.y), pack_bf16(v0.z, v0.w), pack_bf16(v1.x, v1.y), pack_bf16(v1.z, v1.w));
                    sts128(dst + (((hf * 2 + 1) ^ ((r >> 1) & 3)) << 4), pack_bf16(v2.x, v2.y), pack_bf16(v2.z, v2.w), pack_bf16(v3.x, v3.y), pack_bf16(v3.z, v3.w));
                    const uint32_t zz = pack_bf16(z, z);
                    sts128(dst + 4096 + hf * 32, zz, zz, zz, zz);
                    sts128(dst + 4096 + hf * 32 + 16, zz, zz, zz, zz);
                }
            }
            fence_async_smem();
            bar_sync(3, 128);
            const uint32_t stg = base + OFF_G + 32768;
#pragma unroll
            for (int half = 0; half < 2; half++) {
                const int grow = hi * 128 + half * 64 + warp * 16 + (lane >> 2);
                const float g0 = __ldcg(&g_gate[grow]).x, g1 = __ldcg(&g_gate[grow + 8]).x;
#pragma unroll
                for (int j = 0; j < 4; j++) {
                    float p[16];
                    const uint64_t dW = mkdesc(base + OFF_WPHI + 4096 + j * 2048, 16, 512, 2);
                    const uint32_t f0[4] = {pk[half][8 * j], pk[half][8 * j + 1], pk[half][8 * j + 2], pk[half][8 * j + 3]};
                    const uint32_t f1[4] = {pk[half][8 * j + 4], pk[half][8 * j + 5], pk[half][8 * j + 6], pk[half][8 * j + 7]};
                    wg_fence();
                    wgmma_n32_rs_tb(p, f0, dW, 0); wgmma_n32_rs_tb(p, f1, dW + 64, 1);
                    wg_commit(); wg_wait<0>();
                    uint32_t phf[4][4];
                    hedgehog(p, phf);
                    float o[20];
                    const uint64_t dK = mkdesc(base + OFF_G + j * 8192, 4096, 512, 2);
                    wg_fence();
#pragma unroll
                    for (int k = 0; k < 4; k++) wgmma_n40_rs_tb(o, phf[k], dK + k * 64, k != 0);
                    wg_commit(); wg_wait<0>();
                    const float s0 = __fdividef(g0, o[16] + 1e-6f), s1 = __fdividef(g1, o[18] + 1e-6f);
                    const int row = half * 64 + srow;
#pragma unroll
                    for (int q = 0; q < 2; q++) {
                        const int chunk = (j & 1) * 4 + q * 2 + (lane >> 4);
                        stmatrix_x4(stg + (j >> 1) * 16384 + row * 128 + ((chunk ^ (row & 7)) << 4),
                                    pack_bf16(o[8 * q] * s0, o[8 * q + 1] * s0), pack_bf16(o[8 * q + 2] * s1, o[8 * q + 3] * s1),
                                    pack_bf16(o[8 * q + 4] * s0, o[8 * q + 5] * s0), pack_bf16(o[8 * q + 6] * s1, o[8 * q + 7] * s1));
                    }
                }
            }
            fence_async_smem();
            bar_sync(3, 128);
            if (t128 == 0) {
                tma_store_2d(&maps.act, stg, lo * 128, hi * 128);
                tma_store_2d(&maps.act, stg + 16384, lo * 128 + 64, hi * 128);
                bulk_commit();
                bulk_wait_all();
                fence_async_all();
                signal_cnt(cnt_a + hi * 32);
            }
        }
        mainloop_paced();
        {
            int prev = -1;
#pragma unroll 1
            for (int kb = 0; kb < 16; kb++) {
                mbar_wait(bars + B_GFULL + s * 8, ph);
                const uint32_t sa = base + OFF_G + s * 32768;
                const uint64_t dA = mkdesc(sa, 16, 1024, 1), dB = mkdesc(sa + 16384, 8192, 1024, 1);
                wg_fence();
#pragma unroll
                for (int k = 0; k < 4; k++) { wgmma_n128_ss_tb(a0, dA + k * 2, dB + k * 128, 1); wgmma_n128_ss_tb(a1, dA + 512 + k * 2, dB + k * 128, 1); }
                wg_commit();
                if (prev >= 0) { wg_wait<1>(); if (lane == 0) mbar_arrive(bars + B_GEMPTY + prev * 8); }
                prev = s;
                if (++s == GS) { s = 0; ph ^= 1; }
            }
            wg_wait<0>();
            bar_sync(3, 128);
            const uint32_t stg = base + OFF_G;
#pragma unroll
            for (int half = 0; half < 2; half++) {
#pragma unroll
                for (int j = 0; j < 8; j++) {
                    const float* a = half ? a1 : a0;
                    const int row = half * 64 + srow, chunk = (j * 2 + (lane >> 4)) & 7;
                    stmatrix_x4(stg + (j >> 2) * 16384 + row * 128 + ((chunk ^ (row & 7)) << 4),
                                pack_bf16(a[8 * j], a[8 * j + 1]), pack_bf16(a[8 * j + 2], a[8 * j + 3]), pack_bf16(a[8 * j + 4], a[8 * j + 5]), pack_bf16(a[8 * j + 6], a[8 * j + 7]));
                }
            }
            fence_async_smem();
            bar_sync(3, 128);
            if (t128 == 0) {
                tma_store_2d(&maps.out, stg, lo * 128, hi * 128);
                tma_store_2d(&maps.out, stg + 16384, lo * 128 + 64, hi * 128);
                bulk_commit();
                bulk_wait_all();
            }
        }
    } else {
        reg_alloc<144>();
        const float BIAS = 64.f;
        float S0[32], S1[32], O[20];
        uint32_t P0[4][4], P1[4][4];
        int s = 0; uint32_t ph = 0;
        const uint64_t dOnes = mkdesc(base + OFF_ONES, 0, 0, 0);
        const uint64_t dQA = mkdesc(base + OFF_QA + wg * 2048, 128, 256, 0);
        pdl_wait();
        mbar_wait(bars + B_QFULL, 0);
#pragma unroll 1
        for (int it = 0; it < 4; it++) {
            const uint32_t qaddr = base + OFF_Q + (it * 2 + wg) * 4096;
            const uint64_t dQ = mkdesc(qaddr, 16, 512, 2);
            mbar_wait(bars + B_FULL + s * 8, ph);
            {
                const uint64_t dK = mkdesc(base + OFF_KV + s * 16384, 16, 512, 2);
                wg_fence();
                wgmma_n64_ss(S0, dQ, dK, 0); wgmma_n64_ss(S0, dQ + 2, dK + 2, 1);
                wgmma_n64_ss(S1, dQ, dK + 256, 0); wgmma_n64_ss(S1, dQ + 2, dK + 258, 1);
                wg_commit(); wg_wait<0>();
            }
            float m0 = S0[0], m1 = S0[2];
#pragma unroll
            for (int j = 0; j < 8; j++) {
                m0 = fmaxf(m0, fmaxf(S0[4 * j], S0[4 * j + 1])); m1 = fmaxf(m1, fmaxf(S0[4 * j + 2], S0[4 * j + 3]));
                m0 = fmaxf(m0, fmaxf(S1[4 * j], S1[4 * j + 1])); m1 = fmaxf(m1, fmaxf(S1[4 * j + 2], S1[4 * j + 3]));
            }
            m0 = fmaxf(m0, __shfl_xor_sync(~0u, m0, 1)); m0 = fmaxf(m0, __shfl_xor_sync(~0u, m0, 2));
            m1 = fmaxf(m1, __shfl_xor_sync(~0u, m1, 1)); m1 = fmaxf(m1, __shfl_xor_sync(~0u, m1, 2));
            float n0 = -m0 - BIAS, n1 = -m1 - BIAS;
            if (MAXMODE == 2) {
                const uint32_t pk = pack_bf16(n0, n1);
                n0 = bf_lo(pk); n1 = bf_hi(pk);
                if ((lane & 3) == 0) {
                    const int r = warp * 16 + (lane >> 2);
                    *reinterpret_cast<volatile uint16_t*>(base_ptr + OFF_QA + wg * 2048 + (r >> 3) * 256 + (r & 7) * 16) = (uint16_t)(pk & 0xffff);
                    *reinterpret_cast<volatile uint16_t*>(base_ptr + OFF_QA + wg * 2048 + ((r + 8) >> 3) * 256 + (r & 7) * 16) = (uint16_t)(pk >> 16);
                }
                fence_async_smem();
                bar_sync(1 + wg, 128);
            }
#pragma unroll
            for (int j = 0; j < 32; j++) { S0[j] += (j & 2) ? n1 : n0; S1[j] += (j & 2) ? n1 : n0; }
#pragma unroll
            for (int j = 0; j < 20; j++) O[j] = 0.f;
            auto softmax = [&](float (&S)[32], uint32_t (&PP)[4][4]) {
#pragma unroll
                for (int q = 0; q < 16; q++) {
                    if ((POLYMASK >> q) & 1) PP[q >> 2][q & 3] = exp2_pair(S[2 * q], S[2 * q + 1]);
                    else PP[q >> 2][q & 3] = pack_bf16(ex2(S[2 * q]), ex2(S[2 * q + 1]));
                    if (MAXMODE == 1) {
                        asm volatile("prmt.b32 %0, %1, %1, 0x3210;" : "=f"(S[2 * q]) : "f"((q & 1) ? n1 : n0));
                        asm volatile("prmt.b32 %0, %1, %1, 0x3210;" : "=f"(S[2 * q + 1]) : "f"((q & 1) ? n1 : n0));
                    }
                }
            };
            auto qk = [&](float (&S)[32], uint64_t dK) {
                if (MAXMODE == 2) wgmma_n64_ss(S, dQA, dOnes, 0);
                wgmma_n64_ss(S, dQ, dK, 1);
                wgmma_n64_ss(S, dQ + 2, dK + 2, 1);
            };
            auto pv = [&](int st, const int half, uint32_t (&PP)[4][4]) {
                const uint32_t vaddr = base + OFF_KV + st * 16384 + 8192;
                const uint64_t dV0 = mkdesc(vaddr, (base + OFF_ONES) - vaddr, 512, 2);
#pragma unroll
                for (int k4 = 0; k4 < 4; k4++) { const int kk = half * 4 + k4; wgmma_n40_rs_tb(O, PP[k4], dV0 + (uint64_t)kk * 64 - ((uint64_t)kk * 64 << 16), 1); }
            };
            softmax(S0, P0);
#pragma unroll 1
            for (int t = 0; t < 15; t++) {
                int s2 = s + 1; uint32_t ph2 = ph; if (s2 == NS) { s2 = 0; ph2 ^= 1; }
                mbar_wait(bars + B_FULL + s2 * 8, ph2);
                const uint64_t dK = mkdesc(base + OFF_KV + s2 * 16384, 16, 512, 2);
                wg_fence();
                qk(S0, dK); pv(s, 0, P0);
                wg_commit();
                softmax(S1, P1);
                wg_wait<0>();
                wg_fence();
                qk(S1, dK + 256); pv(s, 1, P1);
                wg_commit();
                softmax(S0, P0);
                wg_wait<0>();
                if (lane == 0) mbar_arrive(bars + B_EMPTY + s * 8);
                s = s2; ph = ph2;
            }
            wg_fence();
            pv(s, 0, P0);
            wg_commit();
            softmax(S1, P1);
            wg_fence();
            pv(s, 1, P1);
            wg_commit(); wg_wait<0>();
            if (lane == 0) mbar_arrive(bars + B_EMPTY + s * 8);
            if (++s == NS) { s = 0; ph ^= 1; }
            float chk = 0.f;
#pragma unroll
            for (int j = 0; j < 16; j++) chk = fmaxf(chk, fabsf(O[j]));
            const bool bad = !(O[16] < 1e30f && O[16] > 1e-30f && O[18] < 1e30f && O[18] > 1e-30f && chk < 3e38f) ||
                             (O[0] + O[1] + O[2] + O[3] + O[4] + O[5] + O[6] + O[7] + O[8] + O[9] + O[10] + O[11] + O[12] + O[13] + O[14] + O[15]) !=
                             (O[0] + O[1] + O[2] + O[3] + O[4] + O[5] + O[6] + O[7] + O[8] + O[9] + O[10] + O[11] + O[12] + O[13] + O[14] + O[15]);
            const int row0 = quarter * 512 + it * 128 + wg * 64;
            if (bar_or(1 + wg, 128, bad)) {
                attn_exact(head, row0, qaddr, tid & 127);
            } else {
                const int grow = row0 + warp * 16 + (lane >> 2);
                const float i0 = __ldcg(&g_gate[grow]).y / O[16], i1 = __ldcg(&g_gate[grow + 8]).y / O[18];
                const int row = warp * 16 + (lane & 15);
#pragma unroll
                for (int j = 0; j < 2; j++)
                    stmatrix_x4(qaddr + row * 64 + (((j * 2 + (lane >> 4)) ^ ((row >> 1) & 3)) << 4),
                                pack_bf16(O[8 * j] * i0, O[8 * j + 1] * i0), pack_bf16(O[8 * j + 2] * i1, O[8 * j + 3] * i1),
                                pack_bf16(O[8 * j + 4] * i0, O[8 * j + 5] * i0), pack_bf16(O[8 * j + 6] * i1, O[8 * j + 7] * i1));
            }
            fence_async_smem();
            mbar_arrive(bars + B_ORDY + wg * 8);
        }
    }
}

typedef CUresult (*PFN_encodeTiled)(CUtensorMap*, CUtensorMapDataType, cuuint32_t, void*, const cuuint64_t*, const cuuint64_t*, const cuuint32_t*,
                                    const cuuint32_t*, CUtensorMapInterleave, CUtensorMapSwizzle, CUtensorMapL2promotion, CUtensorMapFloatOOBfill);

CUtensorMap make_map(PFN_encodeTiled enc, const void* ptr, uint64_t inner, uint64_t outer, uint32_t box_inner, uint32_t box_outer, CUtensorMapSwizzle swz) {
    CUtensorMap m;
    cuuint64_t dims[2] = {inner, outer};
    cuuint64_t strides[1] = {inner * 2};
    cuuint32_t box[2] = {box_inner, box_outer};
    cuuint32_t es[2] = {1, 1};
    enc(&m, CU_TENSOR_MAP_DATA_TYPE_BFLOAT16, 2, const_cast<void*>(ptr), dims, strides, box, es, CU_TENSOR_MAP_INTERLEAVE_NONE, swz,
        CU_TENSOR_MAP_L2_PROMOTION_L2_128B, CU_TENSOR_MAP_FLOAT_OOB_FILL_NONE);
    return m;
}

}

extern "C" void kernel_launch(void* const* d_in, const int* in_sizes, int n_in, void* d_out, int out_size) {
    (void)in_sizes; (void)n_in; (void)out_size;
    static PFN_encodeTiled enc = nullptr;
    static void *p_qkv = nullptr, *p_act = nullptr;
    if (!enc) {
        void* p = nullptr;
        cudaDriverEntryPointQueryResult qr;
        cudaGetDriverEntryPoint("cuTensorMapEncodeTiled", &p, cudaEnableDefault, &qr);
        enc = (PFN_encodeTiled)p;
        cudaGetSymbolAddress(&p_qkv, g_qkv);
        cudaGetSymbolAddress(&p_act, g_act);
        cudaFuncSetAttribute(k1_qkv, cudaFuncAttributeMaxDynamicSharedMemorySize, K1_SMEM);
        cudaFuncSetAttribute(k2_fused, cudaFuncAttributeMaxDynamicSharedMemorySize, K2_SMEM);
    }
    const auto SW128 = CU_TENSOR_MAP_SWIZZLE_128B;
    const auto SW64 = CU_TENSOR_MAP_SWIZZLE_64B;
    K1Maps m1;
    m1.x = make_map(enc, d_in[0], 1024, 2048, 64, 256, SW128);
    m1.w = make_map(enc, d_in[5], 3072, 1024, 64, 64, SW128);
    m1.out = make_map(enc, p_qkv, 3072, 2048, 64, 128, SW128);
    K2Maps m2;
    m2.q = make_map(enc, p_qkv, 3072, 2048, 32, 256, SW64);
    m2.kv = make_map(enc, p_qkv, 3072, 2048, 32, 128, SW64);
    m2.ob = make_map(enc, p_act, 2048, 2048, 32, 64, SW64);
    m2.x = make_map(enc, d_in[0], 1024, 2048, 64, 128, SW128);
    m2.wa = make_map(enc, d_in[1], 3072, 1024, 64, 64, SW128);
    m2.phi = make_map(enc, d_in[2], 32, 1024, 32, 64, SW64);
    m2.act = make_map(enc, p_act, 2048, 2048, 64, 128, SW128);
    m2.woa = make_map(enc, d_in[3], 1024, 1024, 64, 64, SW128);
    m2.wob = make_map(enc, d_in[6], 1024, 1024, 64, 64, SW128);
    m2.out = make_map(enc, d_out, 1024, 2048, 64, 128, SW128);

    cudaStream_t st = cudaStreamPerThread;
    k1_qkv<<<128, 384, K1_SMEM, st>>>(m1, (const __nv_bfloat16*)d_in[0], (const __nv_bfloat16*)d_in[7]);
    cudaLaunchConfig_t cfg = {};
    cfg.gridDim = dim3(128); cfg.blockDim = dim3(512); cfg.dynamicSmemBytes = K2_SMEM; cfg.stream = st;
    cudaLaunchAttribute at[1];
    at[0].id = cudaLaunchAttributeProgrammaticStreamSerialization;
    at[0].val.programmaticStreamSerializationAllowed = 1;
    cfg.attrs = at; cfg.numAttrs = 1;
    cudaLaunchKernelEx(&cfg, k2_fused, m2);
}
```

```cpp
#include <cuda_runtime.h>
#include <cuda_bf16.h>
#include <cuda.h>
#include <stdint.h>

#define RA 160
#define RG 160
#define RP 32
#define R1 224
#define PACE 3
#define PACEO 6
#define G2T 2
#define NSLEEP "nanosleep.u32 40;\n"
#define UNR 5
#define POLYMASK 0x1111

namespace {

template <int N> struct IC { static constexpr int value = N; };

constexpr int S_ = 2048;
constexpr float QS = 0.17677669529663687f * 1.4426950408889634f;

__device__ __align__(1024) __nv_bfloat16 g_qkv[S_ * 3072];
__device__ __align__(1024) __nv_bfloat16 g_act[S_ * 2048];
__device__ __align__(1024) float g_kvz[32 * 64 * 32 + 32 * 64];
__device__ __align__(1024) float2 g_gate[S_];
__device__ __align__(1024) uint4 g_kvb[8 * 1280];
__device__ __align__(1024) unsigned g_cnt[89 * 32];
__device__ unsigned g_epoch[128];
constexpr int KVZ_FLOATS = 32 * 64 * 32 + 32 * 64;

#define TS(slot)
#define T2(idx)
__device__ __forceinline__ uint32_t smem_u32(const void* p) { return (uint32_t)__cvta_generic_to_shared(p); }
__device__ __forceinline__ int warp_now() { int t; asm volatile("mov.u32 %0, %%tid.x;" : "=r"(t)); return (t >> 5) & 3; }
__device__ __forceinline__ void wg_fence() { asm volatile("wgmma.fence.sync.aligned;" ::: "memory"); }
__device__ __forceinline__ void wg_commit() { asm volatile("wgmma.commit_group.sync.aligned;" ::: "memory"); }
template <int N> __device__ __forceinline__ void wg_wait() { asm volatile("wgmma.wait_group.sync.aligned %0;" ::"n"(N) : "memory"); }
__device__ __forceinline__ uint64_t mkdesc(uint32_t addr, uint32_t lbo, uint32_t sbo, uint32_t mode) {
    return (uint64_t)((addr & 0x3FFFF) >> 4) | ((uint64_t)(lbo >> 4) << 16) | ((uint64_t)(sbo >> 4) << 32) | ((uint64_t)mode << 62);
}
__device__ __forceinline__ void mbar_init(uint32_t bar, uint32_t cnt) { asm volatile("mbarrier.init.shared::cta.b64 [%0], %1;" ::"r"(bar), "r"(cnt) : "memory"); }
__device__ __forceinline__ void mbar_expect_tx(uint32_t bar, uint32_t bytes) { asm volatile("mbarrier.arrive.expect_tx.shared::cta.b64 _, [%0], %1;" ::"r"(bar), "r"(bytes) : "memory"); }
__device__ __forceinline__ void mbar_arrive(uint32_t bar) { asm volatile("mbarrier.arrive.shared::cta.b64 _, [%0];" ::"r"(bar) : "memory"); }
__device__ __forceinline__ void mbar_wait(uint32_t bar, uint32_t parity) {
    asm volatile("{\n.reg .pred P1;\nLAB_WAIT:\nmbarrier.try_wait.parity.shared::cta.b64 P1, [%0], %1;\n@P1 bra DONE;\nbra LAB_WAIT;\nDONE:\n}" ::"r"(bar), "r"(parity) : "memory");
}
__device__ __forceinline__ void mbar_wait_b(uint32_t bar, uint32_t parity) {
    asm volatile("{\n.reg .pred P1;\n.reg .u32 n;\nmov.u32 n, 0;\n"
                 "LAB_WAIT:\nmbarrier.try_wait.parity.shared::cta.b64 P1, [%0], %1;\n@P1 bra DONE;\n"
                 "add.u32 n, n, 1;\nsetp.gt.u32 P1, n, 4194304;\n@P1 trap;\nbra LAB_WAIT;\nDONE:\n}" ::"r"(bar), "r"(parity) : "memory");
}
__device__ __forceinline__ void tma_load_2d(uint32_t dst, const CUtensorMap* m, uint32_t bar, int c0, int c1) {
    asm volatile("cp.async.bulk.tensor.2d.shared::cluster.global.mbarrier::complete_tx::bytes [%0], [%1, {%3, %4}], [%2];"
                 ::"r"(dst), "l"(m), "r"(bar), "r"(c0), "r"(c1) : "memory");
}
__device__ __forceinline__ void tma_load_2d_mc(uint32_t dst, const CUtensorMap* m, uint32_t bar, int c0, int c1) {
    asm volatile("cp.async.bulk.tensor.2d.shared::cluster.global.mbarrier::complete_tx::bytes.multicast::cluster [%0], [%1, {%3, %4}], [%2], %5;"
                 ::"r"(dst), "l"(m), "r"(bar), "r"(c0), "r"(c1), "h"((uint16_t)3) : "memory");
}
__device__ __forceinline__ void mbar_arrive_cl(uint32_t bar) { asm volatile("mbarrier.arrive.shared::cluster.b64 _, [%0];" ::"r"(bar) : "memory"); }
__device__ __forceinline__ void mbar_arrive_cl_n(uint32_t bar, uint32_t n) { asm volatile("mbarrier.arrive.shared::cluster.b64 _, [%0], %1;" ::"r"(bar), "r"(n) : "memory"); }
__device__ __forceinline__ void tma_store_2d(const CUtensorMap* m, uint32_t src, int c0, int c1) {
    asm volatile("cp.async.bulk.tensor.2d.global.shared::cta.bulk_group [%0, {%2, %3}], [%1];" ::"l"(m), "r"(src), "r"(c0), "r"(c1) : "memory");
}
__device__ __forceinline__ void tma_load_2d_p(bool on, uint32_t dst, const CUtensorMap* m, uint32_t bar, int c0, int c1) {
    asm volatile("{\n.reg .pred p;\nsetp.ne.u32 p, %5, 0;\n@p cp.async.bulk.tensor.2d.shared::cluster.global.mbarrier::complete_tx::bytes [%0], [%1, {%3, %4}], [%2];\n}"
                 ::"r"(dst), "l"(m), "r"(bar), "r"(c0), "r"(c1), "r"((uint32_t)on) : "memory");
}
__device__ __forceinline__ void tma_store_2d_p(bool on, const CUtensorMap* m, uint32_t src, int c0, int c1) {
    asm volatile("{\n.reg .pred p;\nsetp.ne.u32 p, %4, 0;\n@p cp.async.bulk.tensor.2d.global.shared::cta.bulk_group [%0, {%2, %3}], [%1];\n}"
                 ::"l"(m), "r"(src), "r"(c0), "r"(c1), "r"((uint32_t)on) : "memory");
}
__device__ __forceinline__ void mbar_expect_tx_p(bool on, uint32_t bar, uint32_t bytes) {
    asm volatile("{\n.reg .pred p;\nsetp.ne.u32 p, %2, 0;\n@p mbarrier.arrive.expect_tx.shared::cta.b64 _, [%0], %1;\n}" ::"r"(bar), "r"(bytes), "r"((uint32_t)on) : "memory");
}
__device__ __forceinline__ void prefetch_map(const CUtensorMap* m) { asm volatile("prefetch.tensormap [%0];" ::"l"(m) : "memory"); }
__device__ __forceinline__ void bulk_commit() { asm volatile("cp.async.bulk.commit_group;" ::: "memory"); }
__device__ __forceinline__ void bulk_wait_all() { asm volatile("cp.async.bulk.wait_group 0;" ::: "memory"); }
__device__ __forceinline__ void fence_async_smem() { asm volatile("fence.proxy.async.shared::cta;" ::: "memory"); }
__device__ __forceinline__ void fence_async_all() { asm volatile("fence.proxy.async.global;" ::: "memory"); }
__device__ __forceinline__ void bulk_wait_read() { asm volatile("cp.async.bulk.wait_group.read 0;" ::: "memory"); }
__device__ __forceinline__ void mbar_arrive_n(uint32_t bar, uint32_t n) { asm volatile("mbarrier.arrive.shared::cta.b64 _, [%0], %1;" ::"r"(bar), "r"(n) : "memory"); }
__device__ __forceinline__ void bulk_load(uint32_t dst, const void* src, uint32_t bytes, uint32_t bar) {
    asm volatile("cp.async.bulk.shared::cluster.global.mbarrier::complete_tx::bytes [%0], [%1], %2, [%3];" ::"r"(dst), "l"(src), "r"(bytes), "r"(bar) : "memory");
}
__device__ __forceinline__ bool elect_one() {
    uint32_t p;
    asm volatile("{\n.reg .pred P;\nelect.sync _|P, 0xffffffff;\nselp.u32 %0, 1, 0, P;\n}" : "=r"(p));
    return p;
}
__device__ __forceinline__ void bar_sync(int id, int n) { asm volatile("bar.sync %0, %1;" ::"r"(id), "r"(n) : "memory"); }
__device__ __forceinline__ void bar_arrive(int id, int n) { asm volatile("bar.arrive %0, %1;" ::"r"(id), "r"(n) : "memory"); }
__device__ __forceinline__ bool bar_or(int id, int n, bool v) {
    uint32_t r;
    asm volatile("{\n.reg .pred p, q;\nsetp.ne.u32 p, %3, 0;\nbar.red.or.pred q, %1, %2, p;\nselp.u32 %0, 1, 0, q;\n}" : "=r"(r) : "r"(id), "r"(n), "r"((uint32_t)v) : "memory");
    return r;
}
__device__ __forceinline__ uint32_t pack_bf16(float lo, float hi) { uint32_t r; asm("cvt.rn.bf16x2.f32 %0, %1, %2;" : "=r"(r) : "f"(hi), "f"(lo)); return r; }
__device__ __forceinline__ float bf_lo(uint32_t v) { return __uint_as_float(v << 16); }
__device__ __forceinline__ float bf_hi(uint32_t v) { return __uint_as_float(v & 0xffff0000u); }
__device__ __forceinline__ void stmatrix_x4(uint32_t addr, uint32_t r0, uint32_t r1, uint32_t r2, uint32_t r3) {
    asm volatile("stmatrix.sync.aligned.m8n8.x4.shared.b16 [%0], {%1,%2,%3,%4};" ::"r"(addr), "r"(r0), "r"(r1), "r"(r2), "r"(r3) : "memory");
}
__device__ __forceinline__ void stmatrix_x4_t(uint32_t addr, uint32_t r0, uint32_t r1, uint32_t r2, uint32_t r3) {
    asm volatile("stmatrix.sync.aligned.m8n8.x4.trans.shared.b16 [%0], {%1,%2,%3,%4};" ::"r"(addr), "r"(r0), "r"(r1), "r"(r2), "r"(r3) : "memory");
}
__device__ __forceinline__ void ldmatrix_x4(uint32_t (&r)[4], uint32_t addr) {
    asm volatile("ldmatrix.sync.aligned.m8n8.x4.shared.b16 {%0,%1,%2,%3}, [%4];" : "=r"(r[0]), "=r"(r[1]), "=r"(r[2]), "=r"(r[3]) : "r"(addr) : "memory");
}
__device__ __forceinline__ void sts128(uint32_t addr, uint32_t a, uint32_t b, uint32_t c, uint32_t d) {
    asm volatile("st.shared.v4.b32 [%0], {%1,%2,%3,%4};" ::"r"(addr), "r"(a), "r"(b), "r"(c), "r"(d) : "memory");
}
template <int R> __device__ __forceinline__ void reg_alloc() { asm volatile("setmaxnreg.inc.sync.aligned.u32 %0;" ::"n"(R)); }
template <int R> __device__ __forceinline__ void reg_dealloc() { asm volatile("setmaxnreg.dec.sync.aligned.u32 %0;" ::"n"(R)); }
__device__ __forceinline__ float ex2(float x) { float y; asm("ex2.approx.ftz.f32 %0, %1;" : "=f"(y) : "f"(x)); return y; }
__device__ __forceinline__ void signal_cnt(unsigned* c) {
    asm volatile("red.release.gpu.global.add.u32 [%0], 1;" ::"l"(c) : "memory");
}
__device__ __forceinline__ void signal_done(unsigned* c) {
    asm volatile("red.relaxed.gpu.global.add.u32 [%0], 1;" ::"l"(c) : "memory");
}
__device__ __forceinline__ void wait_cnt(const unsigned* c, unsigned per_launch, uint32_t ep) {
    mbar_wait_b(ep, 0);
    asm volatile("{\n.reg .pred P1;\n.reg .u32 n, v, t;\nld.shared.u32 t, [%2+8];\nmul.lo.u32 t, t, %1;\nmov.u32 n, 0;\n"
                 "LAB_WAIT:\nld.acquire.gpu.global.u32 v, [%0];\nsub.u32 v, v, t;\nsetp.ge.s32 P1, v, 0;\n@P1 bra DONE;\n"
                 NSLEEP "add.u32 n, n, 1;\nsetp.gt.u32 P1, n, 8388608;\n@P1 trap;\nbra LAB_WAIT;\nDONE:\n}" ::"l"(c), "r"(per_launch), "r"(ep) : "memory");
}
__device__ __forceinline__ void red_add2(float* p, float a, float b) {
    asm volatile("red.relaxed.gpu.global.add.v2.f32 [%0], {%1, %2};" ::"l"(p), "f"(a), "f"(b) : "memory");
}
__device__ __forceinline__ void red_add1(float* p, float a) {
    asm volatile("red.relaxed.gpu.global.add.f32 [%0], %1;" ::"l"(p), "f"(a) : "memory");
}

__device__ __forceinline__ void wgmma_n192_ss_tb(float (&d)[96], uint64_t descA, uint64_t descB, int scaleD) {
  asm volatile("{\n.reg .pred p;\nsetp.ne.b32 p, %98, 0;\n"
    "wgmma.mma_async.sync.aligned.m64n192k16.f32.bf16.bf16 {%0, %1, %2, %3, %4, %5, %6, %7, %8, %9, %10, %11, %12, %13, %14, %15, %16, %17, %18, %19, %20, %21, %22, %23, %24, %25, %26, %27, %28, %29, %30, %31, %32, %33, %34, %35, %36, %37, %38, %39, %40, %41, %42, %43, %44, %45, %46, %47, %48, %49, %50, %51, %52, %53, %54, %55, %56, %57, %58, %59, %60, %61, %62, %63, %64, %65, %66, %67, %68, %69, %70, %71, %72, %73, %74, %75, %76, %77, %78, %79, %80, %81, %82, %83, %84, %85, %86, %87, %88, %89, %90, %91, %92, %93, %94, %95}, %96, %97, p, 1, 1, 0, 1;\n}\n"
    : "+f"(d[0]), "+f"(d[1]), "+f"(d[2]), "+f"(d[3]), "+f"(d[4]), "+f"(d[5]), "+f"(d[6]), "+f"(d[7]), "+f"(d[8]), "+f"(d[9]), "+f"(d[10]), "+f"(d[11]), "+f"(d[12]), "+f"(d[13]), "+f"(d[14]), "+f"(d[15]), "+f"(d[16]), "+f"(d[17]), "+f"(d[18]), "+f"(d[19]), "+f"(d[20]), "+f"(d[21]), "+f"(d[22]), "+f"(d[23]), "+f"(d[24]), "+f"(d[25]), "+f"(d[26]), "+f"(d[27]), "+f"(d[28]), "+f"(d[29]), "+f"(d[30]), "+f"(d[31]), "+f"(d[32]), "+f"(d[33]), "+f"(d[34]), "+f"(d[35]), "+f"(d[36]), "+f"(d[37]), "+f"(d[38]), "+f"(d[39]), "+f"(d[40]), "+f"(d[41]), "+f"(d[42]), "+f"(d[43]), "+f"(d[44]), "+f"(d[45]), "+f"(d[46]), "+f"(d[47]), "+f"(d[48]), "+f"(d[49]), "+f"(d[50]), "+f"(d[51]), "+f"(d[52]), "+f"(d[53]), "+f"(d[54]), "+f"(d[55]), "+f"(d[56]), "+f"(d[57]), "+f"(d[58]), "+f"(d[59]), "+f"(d[60]), "+f"(d[61]), "+f"(d[62]), "+f"(d[63]), "+f"(d[64]), "+f"(d[65]), "+f"(d[66]), "+f"(d[67]), "+f"(d[68]), "+f"(d[69]), "+f"(d[70]), "+f"(d[71]), "+f"(d[72]), "+f"(d[73]), "+f"(d[74]), "+f"(d[75]), "+f"(d[76]), "+f"(d[77]), "+f"(d[78]), "+f"(d[79]), "+f"(d[80]), "+f"(d[81]), "+f"(d[82]), "+f"(d[83]), "+f"(d[84]), "+f"(d[85]), "+f"(d[86]), "+f"(d[87]), "+f"(d[88]), "+f"(d[89]), "+f"(d[90]), "+f"(d[91]), "+f"(d[92]), "+f"(d[93]), "+f"(d[94]), "+f"(d[95])
    : "l"(descA), "l"(descB), "r"(scaleD));
}
__device__ __forceinline__ void wgmma_n128_ss_tb(float (&d)[64], uint64_t descA, uint64_t descB, int scaleD) {
  asm volatile("{\n.reg .pred p;\nsetp.ne.b32 p, %66, 0;\n"
    "wgmma.mma_async.sync.aligned.m64n128k16.f32.bf16.bf16 {%0, %1, %2, %3, %4, %5, %6, %7, %8, %9, %10, %11, %12, %13, %14, %15, %16, %17, %18, %19, %20, %21, %22, %23, %24, %25, %26, %27, %28, %29, %30, %31, %32, %33, %34, %35, %36, %37, %38, %39, %40, %41, %42, %43, %44, %45, %46, %47, %48, %49, %50, %51, %52, %53, %54, %55, %56, %57, %58, %59, %60, %61, %62, %63}, %64, %65, p, 1, 1, 0, 1;\n}\n"
    : "+f"(d[0]), "+f"(d[1]), "+f"(d[2]), "+f"(d[3]), "+f"(d[4]), "+f"(d[5]), "+f"(d[6]), "+f"(d[7]), "+f"(d[8]), "+f"(d[9]), "+f"(d[10]), "+f"(d[11]), "+f"(d[12]), "+f"(d[13]), "+f"(d[14]), "+f"(d[15]), "+f"(d[16]), "+f"(d[17]), "+f"(d[18]), "+f"(d[19]), "+f"(d[20]), "+f"(d[21]), "+f"(d[22]), "+f"(d[23]), "+f"(d[24]), "+f"(d[25]), "+f"(d[26]), "+f"(d[27]), "+f"(d[28]), "+f"(d[29]), "+f"(d[30]), "+f"(d[31]), "+f"(d[32]), "+f"(d[33]), "+f"(d[34]), "+f"(d[35]), "+f"(d[36]), "+f"(d[37]), "+f"(d[38]), "+f"(d[39]), "+f"(d[40]), "+f"(d[41]), "+f"(d[42]), "+f"(d[43]), "+f"(d[44]), "+f"(d[45]), "+f"(d[46]), "+f"(d[47]), "+f"(d[48]), "+f"(d[49]), "+f"(d[50]), "+f"(d[51]), "+f"(d[52]), "+f"(d[53]), "+f"(d[54]), "+f"(d[55]), "+f"(d[56]), "+f"(d[57]), "+f"(d[58]), "+f"(d[59]), "+f"(d[60]), "+f"(d[61]), "+f"(d[62]), "+f"(d[63])
    : "l"(descA), "l"(descB), "r"(scaleD));
}
__device__ __forceinline__ void wgmma_n64_rs(float (&d)[32], const uint32_t (&a)[4], uint64_t descB, int scaleD) {
  asm volatile("{\n.reg .pred p;\nsetp.ne.b32 p, %37, 0;\n"
    "wgmma.mma_async.sync.aligned.m64n64k16.f32.bf16.bf16 {%0, %1, %2, %3, %4, %5, %6, %7, %8, %9, %10, %11, %12, %13, %14, %15, %16, %17, %18, %19, %20, %21, %22, %23, %24, %25, %26, %27, %28, %29, %30, %31}, {%32, %33, %34, %35}, %36, p, 1, 1, 0;\n}\n"
    : "+f"(d[0]), "+f"(d[1]), "+f"(d[2]), "+f"(d[3]), "+f"(d[4]), "+f"(d[5]), "+f"(d[6]), "+f"(d[7]), "+f"(d[8]), "+f"(d[9]), "+f"(d[10]), "+f"(d[11]), "+f"(d[12]), "+f"(d[13]), "+f"(d[14]), "+f"(d[15]), "+f"(d[16]), "+f"(d[17]), "+f"(d[18]), "+f"(d[19]), "+f"(d[20]), "+f"(d[21]), "+f"(d[22]), "+f"(d[23]), "+f"(d[24]), "+f"(d[25]), "+f"(d[26]), "+f"(d[27]), "+f"(d[28]), "+f"(d[29]), "+f"(d[30]), "+f"(d[31])
    : "r"(a[0]), "r"(a[1]), "r"(a[2]), "r"(a[3]), "l"(descB), "r"(scaleD));
}
__device__ __forceinline__ void wgmma_o192(float (&d)[128], uint64_t descA, uint64_t descB, int scaleD) {
  asm volatile("{\n.reg .pred p;\nsetp.ne.b32 p, %98, 0;\n"
    "wgmma.mma_async.sync.aligned.m64n192k16.f32.bf16.bf16 {%0, %1, %2, %3, %4, %5, %6, %7, %8, %9, %10, %11, %12, %13, %14, %15, %16, %17, %18, %19, %20, %21, %22, %23, %24, %25, %26, %27, %28, %29, %30, %31, %32, %33, %34, %35, %36, %37, %38, %39, %40, %41, %42, %43, %44, %45, %46, %47, %48, %49, %50, %51, %52, %53, %54, %55, %56, %57, %58, %59, %60, %61, %62, %63, %64, %65, %66, %67, %68, %69, %70, %71, %72, %73, %74, %75, %76, %77, %78, %79, %80, %81, %82, %83, %84, %85, %86, %87, %88, %89, %90, %91, %92, %93, %94, %95}, %96, %97, p, 1, 1, 1, 0;\n}\n"
    : "+f"(d[0]), "+f"(d[1]), "+f"(d[2]), "+f"(d[3]), "+f"(d[4]), "+f"(d[5]), "+f"(d[6]), "+f"(d[7]), "+f"(d[8]), "+f"(d[9]), "+f"(d[10]), "+f"(d[11]), "+f"(d[12]), "+f"(d[13]), "+f"(d[14]), "+f"(d[15]), "+f"(d[16]), "+f"(d[17]), "+f"(d[18]), "+f"(d[19]), "+f"(d[20]), "+f"(d[21]), "+f"(d[22]), "+f"(d[23]), "+f"(d[24]), "+f"(d[25]), "+f"(d[26]), "+f"(d[27]), "+f"(d[28]), "+f"(d[29]), "+f"(d[30]), "+f"(d[31]), "+f"(d[32]), "+f"(d[33]), "+f"(d[34]), "+f"(d[35]), "+f"(d[36]), "+f"(d[37]), "+f"(d[38]), "+f"(d[39]), "+f"(d[40]), "+f"(d[41]), "+f"(d[42]), "+f"(d[43]), "+f"(d[44]), "+f"(d[45]), "+f"(d[46]), "+f"(d[47]), "+f"(d[48]), "+f"(d[49]), "+f"(d[50]), "+f"(d[51]), "+f"(d[52]), "+f"(d[53]), "+f"(d[54]), "+f"(d[55]), "+f"(d[56]), "+f"(d[57]), "+f"(d[58]), "+f"(d[59]), "+f"(d[60]), "+f"(d[61]), "+f"(d[62]), "+f"(d[63]), "+f"(d[64]), "+f"(d[65]), "+f"(d[66]), "+f"(d[67]), "+f"(d[68]), "+f"(d[69]), "+f"(d[70]), "+f"(d[71]), "+f"(d[72]), "+f"(d[73]), "+f"(d[74]), "+f"(d[75]), "+f"(d[76]), "+f"(d[77]), "+f"(d[78]), "+f"(d[79]), "+f"(d[80]), "+f"(d[81]), "+f"(d[82]), "+f"(d[83]), "+f"(d[84]), "+f"(d[85]), "+f"(d[86]), "+f"(d[87]), "+f"(d[88]), "+f"(d[89]), "+f"(d[90]), "+f"(d[91]), "+f"(d[92]), "+f"(d[93]), "+f"(d[94]), "+f"(d[95])
    : "l"(descA), "l"(descB), "r"(scaleD));
}
__device__ __forceinline__ void wgmma_o64(float (&d)[128], uint64_t descA, uint64_t descB, int scaleD) {
  asm volatile("{\n.reg .pred p;\nsetp.ne.b32 p, %34, 0;\n"
    "wgmma.mma_async.sync.aligned.m64n64k16.f32.bf16.bf16 {%0, %1, %2, %3, %4, %5, %6, %7, %8, %9, %10, %11, %12, %13, %14, %15, %16, %17, %18, %19, %20, %21, %22, %23, %24, %25, %26, %27, %28, %29, %30, %31}, %32, %33, p, 1, 1, 1, 0;\n}\n"
    : "+f"(d[96]), "+f"(d[97]), "+f"(d[98]), "+f"(d[99]), "+f"(d[100]), "+f"(d[101]), "+f"(d[102]), "+f"(d[103]), "+f"(d[104]), "+f"(d[105]), "+f"(d[106]), "+f"(d[107]), "+f"(d[108]), "+f"(d[109]), "+f"(d[110]), "+f"(d[111]), "+f"(d[112]), "+f"(d[113]), "+f"(d[114]), "+f"(d[115]), "+f"(d[116]), "+f"(d[117]), "+f"(d[118]), "+f"(d[119]), "+f"(d[120]), "+f"(d[121]), "+f"(d[122]), "+f"(d[123]), "+f"(d[124]), "+f"(d[125]), "+f"(d[126]), "+f"(d[127])
    : "l"(descA), "l"(descB), "r"(scaleD));
}
__device__ __forceinline__ void wgmma_t64(float (&d)[32], uint64_t descA, uint64_t descB, int scaleD) {
  asm volatile("{\n.reg .pred p;\nsetp.ne.b32 p, %34, 0;\n"
    "wgmma.mma_async.sync.aligned.m64n64k16.f32.bf16.bf16 {%0, %1, %2, %3, %4, %5, %6, %7, %8, %9, %10, %11, %12, %13, %14, %15, %16, %17, %18, %19, %20, %21, %22, %23, %24, %25, %26, %27, %28, %29, %30, %31}, %32, %33, p, 1, 1, 1, 0;\n}\n"
    : "+f"(d[0]), "+f"(d[1]), "+f"(d[2]), "+f"(d[3]), "+f"(d[4]), "+f"(d[5]), "+f"(d[6]), "+f"(d[7]), "+f"(d[8]), "+f"(d[9]), "+f"(d[10]), "+f"(d[11]), "+f"(d[12]), "+f"(d[13]), "+f"(d[14]), "+f"(d[15]), "+f"(d[16]), "+f"(d[17]), "+f"(d[18]), "+f"(d[19]), "+f"(d[20]), "+f"(d[21]), "+f"(d[22]), "+f"(d[23]), "+f"(d[24]), "+f"(d[25]), "+f"(d[26]), "+f"(d[27]), "+f"(d[28]), "+f"(d[29]), "+f"(d[30]), "+f"(d[31])
    : "l"(descA), "l"(descB), "r"(scaleD));
}
__device__ __forceinline__ void wgmma_n40_rs_tb(float (&d)[20], const uint32_t (&a)[4], uint64_t descB, int scaleD) {
  asm volatile("{\n.reg .pred p;\nsetp.ne.b32 p, %25, 0;\n"
    "wgmma.mma_async.sync.aligned.m64n40k16.f32.bf16.bf16 {%0, %1, %2, %3, %4, %5, %6, %7, %8, %9, %10, %11, %12, %13, %14, %15, %16, %17, %18, %19}, {%20, %21, %22, %23}, %24, p, 1, 1, 1;\n}\n"
    : "+f"(d[0]), "+f"(d[1]), "+f"(d[2]), "+f"(d[3]), "+f"(d[4]), "+f"(d[5]), "+f"(d[6]), "+f"(d[7]), "+f"(d[8]), "+f"(d[9]), "+f"(d[10]), "+f"(d[11]), "+f"(d[12]), "+f"(d[13]), "+f"(d[14]), "+f"(d[15]), "+f"(d[16]), "+f"(d[17]), "+f"(d[18]), "+f"(d[19])
    : "r"(a[0]), "r"(a[1]), "r"(a[2]), "r"(a[3]), "l"(descB), "r"(scaleD));
}
__device__ __forceinline__ void wgmma_n32_ss_tb(float (&d)[16], uint64_t descA, uint64_t descB, int scaleD) {
  asm volatile("{\n.reg .pred p;\nsetp.ne.b32 p, %18, 0;\n"
    "wgmma.mma_async.sync.aligned.m64n32k16.f32.bf16.bf16 {%0, %1, %2, %3, %4, %5, %6, %7, %8, %9, %10, %11, %12, %13, %14, %15}, %16, %17, p, 1, 1, 0, 1;\n}\n"
    : "+f"(d[0]), "+f"(d[1]), "+f"(d[2]), "+f"(d[3]), "+f"(d[4]), "+f"(d[5]), "+f"(d[6]), "+f"(d[7]), "+f"(d[8]), "+f"(d[9]), "+f"(d[10]), "+f"(d[11]), "+f"(d[12]), "+f"(d[13]), "+f"(d[14]), "+f"(d[15])
    : "l"(descA), "l"(descB), "r"(scaleD));
}
__device__ __forceinline__ void wgmma_n40_ss_tatb(float (&d)[20], uint64_t descA, uint64_t descB, int scaleD) {
  asm volatile("{\n.reg .pred p;\nsetp.ne.b32 p, %22, 0;\n"
    "wgmma.mma_async.sync.aligned.m64n40k16.f32.bf16.bf16 {%0, %1, %2, %3, %4, %5, %6, %7, %8, %9, %10, %11, %12, %13, %14, %15, %16, %17, %18, %19}, %20, %21, p, 1, 1, 1, 1;\n}\n"
    : "+f"(d[0]), "+f"(d[1]), "+f"(d[2]), "+f"(d[3]), "+f"(d[4]), "+f"(d[5]), "+f"(d[6]), "+f"(d[7]), "+f"(d[8]), "+f"(d[9]), "+f"(d[10]), "+f"(d[11]), "+f"(d[12]), "+f"(d[13]), "+f"(d[14]), "+f"(d[15]), "+f"(d[16]), "+f"(d[17]), "+f"(d[18]), "+f"(d[19])
    : "l"(descA), "l"(descB), "r"(scaleD));
}
__device__ __forceinline__ void wgmma_n8_rs(float (&d)[4], const uint32_t (&a)[4], uint64_t descB, int scaleD) {
  asm volatile("{\n.reg .pred p;\nsetp.ne.b32 p, %9, 0;\n"
    "wgmma.mma_async.sync.aligned.m64n8k16.f32.bf16.bf16 {%0, %1, %2, %3}, {%4, %5, %6, %7}, %8, p, 1, 1, 0;\n}\n"
    : "+f"(d[0]), "+f"(d[1]), "+f"(d[2]), "+f"(d[3])
    : "r"(a[0]), "r"(a[1]), "r"(a[2]), "r"(a[3]), "l"(descB), "r"(scaleD));
}

__device__ __forceinline__ uint32_t hfma2(uint32_t a, uint32_t b, uint32_t c) { uint32_t d; asm("fma.rn.f16x2 %0, %1, %2, %3;" : "=r"(d) : "r"(a), "r"(b), "r"(c)); return d; }
__device__ __forceinline__ uint32_t exp2_grid(float a, float b) {
    uint32_t w; asm("cvt.pack.sat.s16.s32 %0, %1, %2;" : "=r"(w) : "r"(__float_as_uint(b)), "r"(__float_as_uint(a)));
    uint32_t u = (w & 0x007F007Fu) | 0x64006400u;
    uint32_t f = hfma2(u, 0x20002000u, 0xC800C800u);
    uint32_t q; asm("{.reg .b32 n; neg.f16x2 n, %1; fma.rn.f16x2 %0, %1, %1, n;}" : "=r"(q) : "r"(f));
    uint32_t r = hfma2(f, 0x2d642d64u, 0x34d034d0u);
    uint32_t g = hfma2(q, r, 0x4A004A00u);
    return w + g - 0x4A004A00u;
}
__device__ __forceinline__ float fma_dn(float a, float b, float c) { float d; asm("fma.rn.f32 %0, %1, %2, %3;" : "=f"(d) : "f"(a), "f"(b), "f"(c)); return d; }
__device__ __forceinline__ uint32_t exp2_pair(float x0, float x1) {
    return exp2_grid(fma_dn(x0, __uint_as_float(0x80u), __uint_as_float(0x3F80u)), fma_dn(x1, __uint_as_float(0x80u), __uint_as_float(0x3F80u)));
}
__device__ __forceinline__ uint32_t bmax2(uint32_t a, uint32_t b) { uint32_t d; asm("max.bf16x2 %0, %1, %2;" : "=r"(d) : "r"(a), "r"(b)); return d; }
__device__ __forceinline__ uint32_t bmin2(uint32_t a, uint32_t b) { uint32_t d; asm("min.bf16x2 %0, %1, %2;" : "=r"(d) : "r"(a), "r"(b)); return d; }
__device__ __forceinline__ uint32_t bmul2(uint32_t a, uint32_t b) { uint32_t d; asm("mul.rn.bf16x2 %0, %1, %2;" : "=r"(d) : "r"(a), "r"(b)); return d; }
__device__ __forceinline__ float rcp_fast(float x) { float y; asm("rcp.approx.ftz.f32 %0, %1;" : "=f"(y) : "f"(x)); return y; }

struct K2Maps { CUtensorMap x1, w1, o1, kv, ob, x, wa, phi, act, woa, wob, out, oa; };
constexpr int NS = 4, GS = 3;
constexpr int OFF_G = 0;
constexpr int OFF_KV = GS * 32768;
constexpr int OFF_Q = OFF_KV + NS * 16384;
constexpr int OFF_SPHI = OFF_Q + 32768;
constexpr int OFF_SV = OFF_SPHI + 8192;
constexpr int OFF_WPHI = OFF_SV + 4096;
constexpr int OFF_Z = OFF_WPHI + 4096;
constexpr int OFF_WPHQ = OFF_Z + 4096;
constexpr int OFF_ONES = OFF_WPHQ + 8192;
constexpr int OFF_GATE = OFF_ONES + 1024;
constexpr int OFF_BAR = OFF_GATE + 4096;
constexpr int K2_SMEM = OFF_BAR + 512 + 1024;
constexpr int B_FULL = 0, B_EMPTY = 32, B_GFULL = 64, B_GEMPTY = 96, B_QFULL = 128, B_PHI = 136, B_ORDY = 144, B_DONE = 160, B_KVB = 168, B_ATT = 176, B_CA = 184, B_TE = 192, B_CB = 224, B_OST = 232, B_TF = 256, B_PF = 384, B_PE = 416, B_PS = 448, B_EP = 464, B_QF1 = 480, B_G2 = 488, B_QOK = 496;
constexpr int P_STAGE = 32768 + 24576, OFF_P = 53248;
__device__ __forceinline__ uint32_t p_stg(int wg, int j) { return wg <= 0 ? OFF_KV + j * 16384 : j == 0 ? OFF_KV + 49152 : j == 1 ? OFF_SPHI : OFF_Q + 16384; }

__device__ __forceinline__ uint32_t tail_b(int kb) {
    return OFF_G + ((80 % GS + ((kb < 12 ? kb : kb - 12) >> 2)) % GS) * 32768 + (kb & 3) * 8192;
}

__device__ __forceinline__ void hedgehog(const float (&p)[16], uint32_t (&ph)[4][4]) {
    const float K = 1.4426950408889634f * 1.1754943508222875e-38f;
    uint32_t pk[8];
#pragma unroll
    for (int i = 0; i < 8; i++) pk[i] = pack_bf16(p[2 * i], p[2 * i + 1]);
    float cp[2], cm[2];
#pragma unroll
    for (int r = 0; r < 2; r++) {
        const uint32_t mx = bmax2(bmax2(pk[r], pk[r + 2]), bmax2(pk[r + 4], pk[r + 6]));
        const uint32_t mn = bmin2(bmin2(pk[r], pk[r + 2]), bmin2(pk[r + 4], pk[r + 6])) ^ 0x80008000u;
        uint32_t u = bmax2(__byte_perm(mx, mn, 0x5410), __byte_perm(mx, mn, 0x7632));
        u = bmax2(u, __shfl_xor_sync(~0u, u, 1));
        u = bmax2(u, __shfl_xor_sync(~0u, u, 2));
        cp[r] = fma_dn(bf_lo(u), -K, __uint_as_float(0x3F80u));
        cm[r] = fma_dn(bf_hi(u), -K, __uint_as_float(0x3F80u));
    }
#pragma unroll
    for (int i = 0; i < 8; i++) {
        const float lo = bf_lo(pk[i]), hi = bf_hi(pk[i]);
        ph[i >> 2][i & 3] = exp2_grid(fma_dn(lo, K, cp[i & 1]), fma_dn(hi, K, cp[i & 1]));
        ph[2 + (i >> 2)][i & 3] = exp2_grid(fma_dn(lo, -K, cm[i & 1]), fma_dn(hi, -K, cm[i & 1]));
    }
}

__device__ __forceinline__ void attn_exact(int head, int row0, uint32_t stg, int t) {
    const int r = t >> 1, hf = t & 1;
    float q[32], o[32];
    {
        const uint4* qp = reinterpret_cast<const uint4*>(g_qkv + (size_t)(row0 + r) * 3072 + head * 32);
#pragma unroll
        for (int j = 0; j < 4; j++) {
            const uint4 v = __ldcg(qp + j);
            q[8 * j] = bf_lo(v.x); q[8 * j + 1] = bf_hi(v.x); q[8 * j + 2] = bf_lo(v.y); q[8 * j + 3] = bf_hi(v.y);
            q[8 * j + 4] = bf_lo(v.z); q[8 * j + 5] = bf_hi(v.z); q[8 * j + 6] = bf_lo(v.w); q[8 * j + 7] = bf_hi(v.w);
        }
    }
#pragma unroll
    for (int j = 0; j < 32; j++) o[j] = 0.f;
    float m = -INFINITY, l = 0.f;
#pragma unroll 1
    for (int k = hf * 1024; k < hf * 1024 + 1024; k++) {
        const uint4* kp = reinterpret_cast<const uint4*>(g_qkv + (size_t)k * 3072 + 1024 + head * 32);
        float s = 0.f;
#pragma unroll
        for (int j = 0; j < 4; j++) {
            const uint4 v = kp[j];
            s = fmaf(q[8 * j], bf_lo(v.x), s); s = fmaf(q[8 * j + 1], bf_hi(v.x), s); s = fmaf(q[8 * j + 2], bf_lo(v.y), s); s = fmaf(q[8 * j + 3], bf_hi(v.y), s);
            s = fmaf(q[8 * j + 4], bf_lo(v.z), s); s = fmaf(q[8 * j + 5], bf_hi(v.z), s); s = fmaf(q[8 * j + 6], bf_lo(v.w), s); s = fmaf(q[8 * j + 7], bf_hi(v.w), s);
        }
        s *= QS;
        const float mn = fmaxf(m, s);
        const float c = exp2f(m - mn), p = exp2f(s - mn);
        m = mn; l = l * c + p;
#pragma unroll
        for (int j = 0; j < 4; j++) {
            const uint4 v = kp[128 + j];
            o[8 * j] = fmaf(p, bf_lo(v.x), o[8 * j] * c); o[8 * j + 1] = fmaf(p, bf_hi(v.x), o[8 * j + 1] * c);
            o[8 * j + 2] = fmaf(p, bf_lo(v.y), o[8 * j + 2] * c); o[8 * j + 3] = fmaf(p, bf_hi(v.y), o[8 * j + 3] * c);
            o[8 * j + 4] = fmaf(p, bf_lo(v.z), o[8 * j + 4] * c); o[8 * j + 5] = fmaf(p, bf_hi(v.z), o[8 * j + 5] * c);
            o[8 * j + 6] = fmaf(p, bf_lo(v.w), o[8 * j + 6] * c); o[8 * j + 7] = fmaf(p, bf_hi(v.w), o[8 * j + 7] * c);
        }
    }
    const float m2 = __shfl_xor_sync(~0u, m, 1), mm = fmaxf(m, m2);
    const float c = exp2f(m - mm);
    l *= c; l += __shfl_xor_sync(~0u, l, 1);
    const float sc = __ldcg(&g_gate[row0 + r]).y / l;
#pragma unroll
    for (int j = 0; j < 32; j++) { o[j] *= c; o[j] += __shfl_xor_sync(~0u, o[j], 1); o[j] *= sc; }
#pragma unroll
    for (int c2 = 0; c2 < 2; c2++) {
        uint32_t w[4];
#pragma unroll
        for (int e = 0; e < 4; e++) w[e] = hf ? pack_bf16(o[16 + c2 * 8 + 2 * e], o[16 + c2 * 8 + 2 * e + 1]) : pack_bf16(o[c2 * 8 + 2 * e], o[c2 * 8 + 2 * e + 1]);
        const int chunk = hf * 2 + c2;
        sts128(stg + r * 64 + ((chunk ^ ((r >> 1) & 3)) << 4), w[0], w[1], w[2], w[3]);
    }
}

__global__ void __launch_bounds__(512, 1) k2_fused(const __grid_constant__ K2Maps maps, const __nv_bfloat16* __restrict__ x, const __nv_bfloat16* __restrict__ gate_w) {
    extern __shared__ uint8_t smem_raw[];
    const uint32_t base = (smem_u32(smem_raw) + 1023) & ~1023u;
    uint8_t* base_ptr = smem_raw + (base - smem_u32(smem_raw));
    const uint32_t bars = base + OFF_BAR;
    const int tid = threadIdx.x, wg = __shfl_sync(~0u, tid >> 7, 0), lane = tid & 31;
    const int cta = blockIdx.x;
    const int head = cta >> 2, quarter = cta & 3;
    const int hi = cta >> 3, lo = cta & 7;
    const int orow = (cta >> 5) * 512 + ((cta >> 4) & 1) * 64, ocol = (cta & 15) * 64, oq = (cta >> 5) * 4;
    unsigned* const cnt_kv = g_cnt, * const cnt_a = g_cnt + 16 * 32, * const cnt_b = g_cnt + 32 * 32, * const cnt_kvb = g_cnt + 48 * 32, * const cnt_q = g_cnt + 56 * 32, * const cnt_g = g_cnt + 88 * 32;
    const uint32_t ep = bars + B_EP;
    auto p_load = [&](int kb, int s) {
        const uint32_t fb = bars + B_PF + s * 8, sa = base + OFF_P + s * P_STAGE;
        mbar_expect_tx(fb, P_STAGE);
        tma_load_2d(sa, &maps.x1, fb, kb * 64, lo * 256);
#pragma unroll 1
        for (int j = 0; j < 3; j++) tma_load_2d(sa + 32768 + j * 8192, &maps.w1, fb, hi * 192 + j * 64, kb * 64);
    };
    if (tid == 416) {
        for (int s = 0; s < 3; s++) { mbar_init(bars + B_PF + s * 8, 1); mbar_init(bars + B_PE + s * 8, 8); }
        fence_async_smem();
#pragma unroll 1
        for (int kb = 0; kb < 3; kb++) p_load(kb, kb ? kb - 1 : 2);
    }
    if (tid == 384) {
        for (int s = 0; s < NS; s++) { mbar_init(bars + B_FULL + s * 8, 1); mbar_init(bars + B_EMPTY + s * 8, 8); }
        for (int s = 0; s < GS; s++) { mbar_init(bars + B_GFULL + s * 8, 1); mbar_init(bars + B_GEMPTY + s * 8, 8); }
        mbar_init(bars + B_DONE, 4); mbar_init(bars + B_QFULL, 1); mbar_init(bars + B_PHI, 1); mbar_init(bars + B_KVB, 1); mbar_init(bars + B_ATT, 4); mbar_init(bars + B_CA, 4); mbar_init(bars + B_CB, 3); mbar_init(bars + B_OST, 4);
        for (int s = 0; s < 4; s++) mbar_init(bars + B_TE + s * 8, 8);
        for (int s = 0; s < 16; s++) mbar_init(bars + B_TF + s * 8, 2);
        mbar_init(bars + B_PS, 1); mbar_init(bars + B_PS + 8, 1); mbar_init(ep, 1); mbar_init(bars + B_QF1, 1); mbar_init(bars + B_G2, 1); mbar_init(bars + B_QOK, 4); mbar_init(bars + B_QOK + 8, 4);
        mbar_init(bars + B_ORDY, 128); mbar_init(bars + B_ORDY + 8, 128);
        asm volatile("fence.mbarrier_init.release.cluster;" ::: "memory");
    }
    if (tid < 256) reinterpret_cast<uint32_t*>(base_ptr + OFF_ONES)[tid] = 0x3F803F80u;
    fence_async_smem();
    asm volatile("barrier.cluster.arrive.relaxed.aligned;" ::: "memory");
    __syncthreads();
    asm volatile("barrier.cluster.wait.aligned;" ::: "memory");
    uint32_t peer;
    asm("mapa.shared::cluster.u32 %0, %1, %2;" : "=r"(peer) : "r"(bars), "r"((cta & 1) ^ 1));
    peer -= bars;
    if (tid == 0) TS(0);

    if (wg == 3) {
        reg_dealloc<RP>();
        const int warp = __shfl_sync(~0u, (tid >> 5) & 3, 0);
        if (warp == 3) {
#pragma unroll 1
            for (int w = -1; w < 2; w++) {
                if (w == 1) mbar_wait_b(bars + B_G2, 0);
#pragma unroll 1
                for (int j = 0; j < 3; j++) {
                    if (w >= 0) bar_sync(8 + w * 3 + j, 160);
                    tma_store_2d_p(w >= 0 && lane == 0, &maps.o1, base + p_stg(w, j), hi * 192 + j * 64, lo * 256 + w * 128);
                }
                if (lane == 0) {
                    bulk_commit();
                    bulk_wait_all();
                    asm volatile("{\n.reg .pred p;\nsetp.ge.s32 p, %2, 0;\n@p red.relaxed.gpu.global.add.u32 [%0], 1;\n@p mbarrier.arrive.shared::cta.b64 _, [%1];\n}"
                                 ::"l"(cnt_q + hi * 64 + w * 32), "r"(bars + B_PS + w * 8), "r"(w) : "memory");
                    if (w >= 0) TS(w ? 3 : 28);
                }
                __syncwarp();
            }
        }
        if (warp == 2) {
#pragma unroll 1
            for (int w = 0; w < 2; w++)
                if (lane < 4) {
                    wait_cnt(lane == 3 ? cnt_g : cnt_q + ((lane * 32 + head) / 6) * 64 + w * 32, lane == 3 ? 128 : 8, ep);
                    mbar_arrive(bars + B_QOK + w * 8);
                }
            __syncwarp();
        }
        if (warp < 2) {
            if (!elect_one()) {
            } else if (warp == 0) {
                prefetch_map(&maps.kv); prefetch_map(&maps.phi); prefetch_map(&maps.o1);
                int s = 0; uint32_t ph = 1;
#pragma unroll 1
                for (int T = -1; T < 64; T++) {
                    mbar_wait_b(bars + B_EMPTY + s * 8, ph);
                    if (T <= 0) {
                        if (T == 0) { mbar_wait_b(bars + B_QOK, 0); mbar_wait_b(bars + B_PS, 0); mbar_wait_b(bars + B_PE + 16, 1); TS(4); }
                        fence_async_all();
                        mbar_expect_tx_p(T == 0, bars + B_QFULL, 8192);
                        tma_load_2d_p(T == 0, base + OFF_Q, &maps.kv, bars + B_QFULL, head * 32, quarter * 512);
                    }
                    if (T == G2T) mbar_arrive(bars + B_G2);
                    if (T == 2) {
                        bulk_load(base + OFF_GATE, g_gate + quarter * 512, 4096, bars + B_FULL + 16);
                    }
                    if (T == 3) {
                        mbar_wait_b(bars + B_PS + 8, 0);
                        mbar_expect_tx(bars + B_PHI, 12288);
                        tma_load_2d(base + OFF_WPHI, &maps.phi, bars + B_PHI, 0, hi * 64);
                        tma_load_2d(base + OFF_WPHQ, &maps.phi, bars + B_PHI, 0, lo * 128);
                        tma_load_2d(base + OFF_WPHQ + 4096, &maps.phi, bars + B_PHI, 0, lo * 128 + 64);
                    }
                    if (T == 8) {
                        mbar_wait_b(bars + B_QOK + 8, 0);
                        fence_async_all();
                        mbar_expect_tx(bars + B_QF1, 24576);
#pragma unroll 1
                        for (int m = 1; m < 4; m++) tma_load_2d(base + OFF_Q + m * 8192, &maps.kv, bars + B_QF1, head * 32, quarter * 512 + m * 128);
                    }
                    const uint32_t fb = bars + B_FULL + s * 8, dst = base + OFF_KV + s * 16384;
                    const int key = (T & 7) * 256 + (T & 8) * 16;
                    mbar_expect_tx_p(T >= 0, fb, T == 2 ? 20480 : 16384);
                    tma_load_2d_p(T >= 0, dst, &maps.kv, fb, 1024 + head * 32, key);
                    tma_load_2d_p(T >= 0, dst + 8192, &maps.kv, fb, 2048 + head * 32, key);
                    if (T >= 0 && ++s == NS) { s = 0; ph ^= 1; }
                }
#pragma unroll 1
                for (int kb = 0; kb < 20; kb++) mbar_expect_tx(bars + B_TF + (kb < 16 ? kb : kb - 4) * 8, 8192);
                mbar_wait_b(bars + B_ATT, 0);
                T2(183);
                wait_cnt(cnt_b + (oq + 3) * 32, 64, ep);
                TS(23);
                T2(182);
                fence_async_all();
#pragma unroll 1
                for (int kb = cta & 1; kb < 12; kb += 2) tma_load_2d_mc(base + OFF_KV + kb * 8192, &maps.act, bars + B_TF + kb * 8, 1024 + kb * 64, orow + 384);
#pragma unroll 1
                for (int kb = 12; kb < 16; kb++) {
                    mbar_wait_b(bars + B_TE + (kb - 12) * 8, 0);
                    if (((kb ^ cta) & 1) == 0) tma_load_2d_mc(base + OFF_KV + (kb - 12) * 8192, &maps.act, bars + B_TF + kb * 8, 1024 + kb * 64, orow + 384);
                    tma_load_2d(base + tail_b(kb), &maps.wob, bars + B_TF + kb * 8, ocol, kb * 64);
                }
                T2(184);
                mbar_wait_b(bars + B_DONE, 0);
            } else if (warp == 1) {
                int s = 2; uint32_t ph = 0;
#pragma unroll 1
                for (int kb = 3; kb < 16; kb++) {
                    mbar_wait_b(bars + B_PE + s * 8, ph);
                    p_load(kb, s);
                    if (s == 1) ph ^= 1;
                    if (++s == 3) s = 0;
                }
                mbar_wait_b(bars + B_PE, ph);
                s = 0; ph = 1;
#pragma unroll 1
                for (int i = 0; i < 48; i++) {
                    const int t = i >> 4, kb = i & 15;
                    const int row = (t < 2) ? lo * 256 + t * 128 : hi * 128;
                    const int c0 = (t < 2) ? 1024 + hi * 64 : lo * 128, c1 = (t < 2) ? 2048 + hi * 64 : lo * 128 + 64;
                    mbar_wait_b(bars + B_GEMPTY + s * 8, ph);
                    const uint32_t fb = bars + B_GFULL + s * 8, sa = base + OFF_G + s * 32768;
                    mbar_expect_tx(fb, 32768);
                    tma_load_2d(sa, &maps.x, fb, kb * 64, row);
                    tma_load_2d(sa + 16384, &maps.wa, fb, c0, kb * 64);
                    tma_load_2d(sa + 24576, &maps.wa, fb, c1, kb * 64);
                    if (++s == GS) { s = 0; ph ^= 1; }
                }
                wait_cnt(cnt_kvb + lo * 32, 32, ep);
                fence_async_all();
                mbar_expect_tx(bars + B_KVB, 20480);
                bulk_load(base + OFF_SPHI, g_kvb + lo * 1280, 20480, bars + B_KVB);
#pragma unroll 1
                for (int i = 0; i < 32; i++) {
                    const int kb = i & 15, nb = 4 - (i >> 4);
                    mbar_wait_b(bars + B_GEMPTY + s * 8, ph);
                    T2(64 + i * 2);
                    const uint32_t fb = bars + B_GFULL + s * 8, sa = base + OFF_G + s * 32768;
                    if (kb == 0) {
                        mbar_wait_b(bars + (i ? B_CB : B_CA), 0);
                        TS(20 + (i >> 4));
                        fence_async_all();
                    }
                    mbar_expect_tx(fb, nb * 8192 + 8192);
                    tma_load_2d(i < 16 ? base + OFF_SPHI + s * 8192 : sa + 24576, i < 16 ? &maps.woa : &maps.wob, fb, ocol, kb * 64);
#pragma unroll 1
                    for (int m = (kb ^ cta) & 1; m < nb; m += 2) tma_load_2d_mc(sa + m * 8192, &maps.act, fb, (i < 16 ? 0 : 1024) + kb * 64, orow + m * 128);
                    T2(64 + i * 2 + 1);
                    if (++s == GS) { s = 0; ph ^= 1; }
                }
#pragma unroll 1
                for (int kb = 0; kb < 12; kb++) {
                    if ((kb & 3) == 0) { mbar_wait_b(bars + B_GEMPTY + s * 8, ph); if (++s == GS) { s = 0; ph ^= 1; } }
                    mbar_expect_tx(bars + B_TF + kb * 8, 8192);
                    tma_load_2d(base + tail_b(kb), &maps.wob, bars + B_TF + kb * 8, ocol, kb * 64);
                }
                mbar_wait_b(bars + B_OST, 0);
#pragma unroll 1
                for (int m = 0; m < 3; m++) tma_store_2d(&maps.out, base + OFF_SPHI + m * 8192, ocol, orow + m * 128);
                bulk_commit();
                bulk_wait_all();
            }
        }
        if (warp >= 2) {
            const int w = warp - 2;
#pragma unroll 1
            for (int it = 0; it < 4; it++) {
                if (elect_one()) {
                    mbar_wait_b(bars + B_ORDY + w * 8, it & 1);
                    if (it == 3) T2(187 + w * 3);
                    tma_store_2d(&maps.ob, base + OFF_Q + (it * 2 + w) * 4096, 1024 + head * 32, quarter * 512 + it * 128 + w * 64);
                    bulk_commit();
                    bulk_wait_all();
                    if (it == 3) T2(188 + w * 3);
                    signal_done(cnt_b + (quarter * 4 + it) * 32);
                    if (it == 3) T2(189 + w * 3);
                    if (it == 1) wait_cnt(cnt_kv + hi * 32, 8, ep);
                    if (it == 3) { mbar_arrive(bars + B_ATT); mbar_arrive_cl(bars + B_ATT + peer); }
                }
                __syncwarp();
                if (it == 2 && w == 0 && lane < 3) { wait_cnt(cnt_b + (oq + lane) * 32, 64, ep); mbar_arrive(bars + B_CB); }
                if (it == 1) {
                    int ln = lane;
                    asm volatile("" : "+r"(ln));
                    const int h = hi * 2 + w, f = lo * 8 + (ln >> 2), c = ln & 3;
                    const float4* src = reinterpret_cast<const float4*>(g_kvz + (h * 64 + f) * 32 + c * 8);
                    const float4 v0 = __ldcg(src), v1 = __ldcg(src + 1);
                    const float z = __ldcg(g_kvz + 65536 + h * 64 + f);
                    uint4* img = g_kvb + (h >> 2) * 1280 + f * 4;
                    img[(h & 3) * 256 + (c ^ ((f >> 1) & 3))] = make_uint4(pack_bf16(v0.x, v0.y), pack_bf16(v0.z, v0.w), pack_bf16(v1.x, v1.y), pack_bf16(v1.z, v1.w));
                    const uint32_t zz = pack_bf16(z, 1.0f);
                    if (c == 0) img[1024 + ((h & 3) ^ ((f >> 1) & 3))] = make_uint4(zz, zz, zz, zz);
                    fence_async_all();
                    __syncwarp();
                    if (lane == 0) signal_cnt(cnt_kvb + (h >> 2) * 32);
                    if (w == 1 && lane < 4) { wait_cnt(cnt_a + (oq + lane) * 32, 8, ep); mbar_arrive(bars + B_CA); }
                }
            }
        }
    } else if (wg == 2) {
        const int t128 = tid & 127;
        reg_dealloc<RP>();
        {
            if (t128 == 0) {
                const unsigned e = g_epoch[cta] + 1;
                g_epoch[cta] = e;
                asm volatile("st.shared.u32 [%0+8], %1;" ::"r"(ep), "r"(e) : "memory");
                mbar_arrive(ep);
            }
            constexpr int ZPER = KVZ_FLOATS / 4 / 128;
            for (int i = t128; i < ZPER; i += 128) reinterpret_cast<float4*>(g_kvz)[cta * ZPER + i] = make_float4(0.f, 0.f, 0.f, 0.f);
#pragma unroll 1
            for (int r = warp_now(); r < 16; r += 4) {
                const int row = cta * 16 + r;
                float acc = 0.f;
#pragma unroll 2
                for (int j = 0; j < 4; j++) {
                    const uint4 xv = __ldg(reinterpret_cast<const uint4*>(x + (size_t)row * 1024) + j * 32 + lane);
                    const uint4 wv = __ldg(reinterpret_cast<const uint4*>(gate_w) + j * 32 + lane);
                    const uint32_t xa[4] = {xv.x, xv.y, xv.z, xv.w}, wa[4] = {wv.x, wv.y, wv.z, wv.w};
#pragma unroll
                    for (int e = 0; e < 4; e++) {
                        const uint32_t p = pack_bf16(bf_lo(xa[e]) * bf_lo(wa[e]), bf_hi(xa[e]) * bf_hi(wa[e]));
                        acc += bf_lo(p); acc += bf_hi(p);
                    }
                }
#pragma unroll
                for (int o = 16; o; o >>= 1) acc += __shfl_xor_sync(~0u, acc, o);
                if (lane == 0) {
                    const float sb = __bfloat162float(__float2bfloat16(acc));
                    const float g = __bfloat162float(__float2bfloat16(1.0f / (1.0f + __expf(-sb))));
                    g_gate[row] = make_float2(g, __bfloat162float(__float2bfloat16(1.0f - g)));
                    fence_async_all();
                }
            }
            bar_sync(3, 128);
            if (t128 == 0) signal_cnt(cnt_g);
        }
        reg_alloc<RG>();
        const int warp = warp_now();
        const int srow = warp * 16 + (lane & 15);
        int s = 0; uint32_t ph = 0;
#pragma unroll 1
        for (int t = 0; t < 3; t++) {
            uint32_t stg;
            float gq[4];
            {
                float a0[64], a1[64];
#pragma unroll
                for (int i = 0; i < 64; i++) { a0[i] = 0.f; a1[i] = 0.f; }
#pragma unroll 1
                for (int kb = 0; kb < 16; kb++) {
                    mbar_wait(bars + B_GFULL + s * 8, ph);
                    const uint32_t sa = base + OFF_G + s * 32768;
                    const uint64_t dA = mkdesc(sa, 16, 1024, 1), dB = mkdesc(sa + 16384, 8192, 1024, 1);
#pragma unroll
                    for (int k = 0; k < 4; k++) {
                        if (PACE == 2 || k == 0 || (PACE == 4 && k == 2) || (PACE == 3 && k < 3) || PACE == 6) wg_fence();
                        wgmma_n128_ss_tb(a0, dA + k * 2, dB + k * 128, 1);
                        wgmma_n128_ss_tb(a1, dA + 512 + k * 2, dB + k * 128, 1);
                        if (PACE == 2 || k == 3 || (PACE == 4 && k == 1) || (PACE == 3 && k < 2)) { wg_commit(); wg_wait<0>(); }
                        else if (PACE == 6) { wg_commit(); wg_wait<1>(); }
                    }
                    if (lane == 0 && kb < 15) {
                        mbar_arrive(bars + B_GEMPTY + s * 8);
                        mbar_arrive_cl(bars + B_GEMPTY + s * 8 + ((t == 2 && kb >= 13) ? peer : 0u));
                    }
                    stg = sa;
                    if (++s == GS) { s = 0; ph ^= 1; }
                }
                if (t128 == 0) TS(5 + 2 * t);
                if (t == 2) {
#pragma unroll
                    for (int i = 0; i < 4; i++) gq[i] = __ldcg(&g_gate[hi * 128 + (i >> 1) * 64 + warp * 16 + (lane >> 2) + (i & 1) * 8]).x;
                }
                bar_sync(3, 128);
#pragma unroll
                for (int half = 0; half < 2; half++) {
                    const float* a = half ? a1 : a0;
                    const int row = half * 64 + srow;
#pragma unroll
                    for (int g = 0; g < 8; g++)
                        stmatrix_x4(stg + (g >> 1) * 8192 + row * 64 + ((((g & 1) * 2 + (lane >> 4)) ^ ((row >> 1) & 3)) << 4),
                                    pack_bf16(a[8 * g], a[8 * g + 1]), pack_bf16(a[8 * g + 2], a[8 * g + 3]), pack_bf16(a[8 * g + 4], a[8 * g + 5]), pack_bf16(a[8 * g + 6], a[8 * g + 7]));
                }
            }
            fence_async_smem();
            bar_sync(3, 128);
            {
                if (t == 0) {
                    mbar_wait(bars + B_PHI, 0);
#pragma unroll 1
                    for (int i = 0; i < 6; i++) {
                        uint4* w = reinterpret_cast<uint4*>(base_ptr + (i < 2 ? OFF_WPHI : OFF_WPHQ - 4096) + i * 2048) + t128;
                        uint4 v = *w;
                        v.x = bmul2(v.x, 0x37803780u); v.y = bmul2(v.y, 0x37803780u); v.z = bmul2(v.z, 0x37803780u); v.w = bmul2(v.w, 0x37803780u);
                        *w = v;
                    }
                    fence_async_smem();
                    if (t128 == 0) wait_cnt(cnt_g, 128, ep);
                    bar_sync(3, 128);
                }
                if (t == 2) {
                    mbar_wait(bars + B_KVB, 0);
                    if (t128 == 0) TS(10);
                }
                const int nun = t < 2 ? 2 : 4;
#pragma unroll 1
                for (int j = 0; j < nun; j++) {
                    const uint32_t blk = stg + j * 8192;
                    uint32_t phf[2][4][4];
                    {
                        float p0[16], p1[16];
                        const uint64_t dX = mkdesc(blk, 16, 512, 2), dW = mkdesc(base + (t < 2 ? OFF_WPHI : OFF_WPHQ) + j * 2048, 16, 512, 2);
                        wg_fence();
                        wgmma_n32_ss_tb(p0, dX, dW, 0); wgmma_n32_ss_tb(p1, dX + 256, dW, 0);
                        wgmma_n32_ss_tb(p0, dX + 2, dW + 64, 1); wgmma_n32_ss_tb(p1, dX + 258, dW + 64, 1);
                        wg_commit(); wg_wait<0>();
                        hedgehog(p0, phf[0]);
                        hedgehog(p1, phf[1]);
                    }
                    if (t < 2) {
                        float sm[4][4];
                        const uint64_t dOne = mkdesc(base + OFF_ONES, 0, 0, 0);
                        wg_fence();
#pragma unroll
                        for (int i = 0; i < 8; i++) { const int k = (i & 3) * 2 + (i >> 2); wgmma_n8_rs(sm[k >> 1], phf[k >> 2][k & 3], dOne, k & 1); }
                        wg_commit(); wg_wait<0>();
#pragma unroll
                        for (int k = 0; k < 4; k++) {
                            const float r0 = rcp_fast(sm[k][0]), r1 = rcp_fast(sm[k][2]);
                            const uint32_t n0 = pack_bf16(r0, r0), n1 = pack_bf16(r1, r1);
#pragma unroll
                            for (int e = 0; e < 8; e++) { uint32_t& x = phf[k >> 1][(k & 1) * 2 + (e >> 2)][e & 3]; x = bmul2(x, (e & 1) ? n1 : n0); }
                        }
                        bar_sync(3, 128);
#pragma unroll
                        for (int half = 0; half < 2; half++)
#pragma unroll
                            for (int q = 0; q < 4; q++)
                                stmatrix_x4((half ? blk : base + OFF_SPHI) + srow * 128 + (((q * 2 + (lane >> 4)) ^ (srow & 7)) << 4),
                                            phf[half][q][0], phf[half][q][1], phf[half][q][2], phf[half][q][3]);
                        fence_async_smem();
                        bar_sync(3, 128);
                        float kv[20], kw[20];
                        const uint64_t dP0 = mkdesc(base + OFF_SPHI, 16, 1024, 1), dP1 = mkdesc(blk, 16, 1024, 1);
                        const uint64_t dV = mkdesc(blk + 16384, base + OFF_ONES - (blk + 16384), 512, 2);
                        wg_fence();
#pragma unroll
                        for (int k = 0; k < 4; k++) {
                            wgmma_n40_ss_tatb(kv, dP0 + k * 128, dV + (uint64_t)k * 64 - ((uint64_t)k * 64 << 16), k != 0);
                            wgmma_n40_ss_tatb(kw, dP1 + k * 128, dV + (uint64_t)(k + 4) * 64 - ((uint64_t)(k + 4) * 64 << 16), k != 0);
                        }
                        wg_commit(); wg_wait<0>();
#pragma unroll
                        for (int i = 0; i < 20; i++) kv[i] += kw[i];
                        const int h = hi * 2 + j, f = warp * 16 + (lane >> 2);
                        float* dst = g_kvz + (h * 64 + f) * 32 + (lane & 3) * 2;
#pragma unroll
                        for (int q = 0; q < 4; q++) { red_add2(dst + q * 8, kv[4 * q], kv[4 * q + 1]); red_add2(dst + 256 + q * 8, kv[4 * q + 2], kv[4 * q + 3]); }
                        if ((lane & 3) == 0) { red_add1(g_kvz + 65536 + h * 64 + f, kv[16]); red_add1(g_kvz + 65536 + h * 64 + f + 8, kv[18]); }
                    } else {
                        float o[4][20];
                        const uint64_t dK = mkdesc(base + OFF_SPHI + j * 4096, OFF_Z - OFF_SPHI - j * 4096 + j * 16, 512, 2);
                        wg_fence();
#pragma unroll
                        for (int i = 0; i < 8; i++) { const int k = (i & 3) * 2 + (i >> 2); wgmma_n40_rs_tb(o[k >> 1], phf[k >> 2][k & 3], dK + (k & 3) * 64, k & 1); }
                        wg_commit(); wg_wait<0>();
#pragma unroll
                        for (int half = 0; half < 2; half++) {
                            const float* op = o[half * 2], * om = o[half * 2 + 1];
                            float ap[2], am[2];
#pragma unroll
                            for (int r = 0; r < 2; r++) {
                                const float ip = rcp_fast(op[17 + 2 * r]), im = rcp_fast(om[17 + 2 * r]);
                                const float sc = __fdividef(gq[half * 2 + r], fmaf(op[16 + 2 * r], ip, fmaf(om[16 + 2 * r], im, 1e-6f)));
                                ap[r] = ip * sc; am[r] = im * sc;
                            }
                            uint32_t w[8];
#pragma unroll
                            for (int i = 0; i < 8; i++)
                                w[i] = pack_bf16(fmaf(op[2 * i], ap[i & 1], om[2 * i] * am[i & 1]), fmaf(op[2 * i + 1], ap[i & 1], om[2 * i + 1] * am[i & 1]));
                            const int row = half * 64 + srow;
#pragma unroll
                            for (int q = 0; q < 2; q++)
                                stmatrix_x4(blk + row * 64 + (((q * 2 + (lane >> 4)) ^ ((row >> 1) & 3)) << 4), w[4 * q], w[4 * q + 1], w[4 * q + 2], w[4 * q + 3]);
                        }
                        fence_async_smem();
                        bar_sync(3, 128);
                        tma_store_2d_p(t128 == 0, &maps.oa, blk, lo * 128 + j * 32, hi * 128);
                    }
                }
                if (t < 2) bar_sync(3, 128);
            }
            if (t128 == 0) {
                const uint32_t eb = bars + B_GEMPTY + (s == 0 ? GS - 1 : s - 1) * 8;
                if (t < 2) {
                    mbar_arrive_n(eb, 8);
                    if (t == 1) signal_cnt(cnt_kv + hi * 32);
                    TS(6 + 2 * t);
                } else {
                    bulk_commit();
                    bulk_wait_read();
                    mbar_arrive_n(eb, 4);
                    mbar_arrive_cl_n(eb + peer, 4);
                    bulk_wait_all();
                    signal_done(cnt_a + hi * 32);
                    TS(11);
                }
            }
            __syncwarp();
        }
        float c[128];
#pragma unroll
        for (int i = 0; i < 128; i++) c[i] = 0.f;
        auto release = [&](int st) { mbar_arrive(bars + B_GEMPTY + st * 8); mbar_arrive_cl(bars + B_GEMPTY + st * 8 + peer); };
        auto out_pass = [&](auto nbc) {
            constexpr int NB = decltype(nbc)::value;
#pragma unroll 1
            for (int kb = 0; kb < 16; kb++) {
                mbar_wait(bars + B_GFULL + s * 8, ph);
                if (t128 == 0) T2((4 - NB) * 32 + kb * 2);
                const uint32_t sa = base + OFF_G + s * 32768;
                const uint64_t dX = mkdesc(sa, 16, 1024, 1), dW = mkdesc(NB == 3 ? sa + 24576 : base + OFF_SPHI + s * 8192, 16, 1024, 1);
#pragma unroll
                for (int k = 0; k < 4; k++) {
                    if (PACEO == 2 || k == 0 || ((PACEO == 4 || PACEO == 8) && k == 2) || PACEO == 6 || PACEO == 7) wg_fence();
                    wgmma_o192(c, dW + k * 128, dX + k * 2, 1);
                    if (NB == 4) wgmma_o64(c, dW + k * 128, dX + 1536 + k * 2, 1);
                    if (PACEO >= 7) {
                        if (PACEO == 7 || (PACEO == 8 && (k & 1)) || k == 3) {
                            wg_commit(); wg_wait<1>();
                            if (k == (PACEO == 7 ? 0 : PACEO == 8 ? 1 : 3) && lane == 0 && kb > 0) release(s == 0 ? GS - 1 : s - 1);
                        }
                    } else if (PACEO == 2 || k == 3 || (PACEO == 4 && k == 1)) { wg_commit(); wg_wait<0>(); }
                    else if (PACEO == 6) { wg_commit(); wg_wait<1>(); }
                }
                if (PACEO < 7 && lane == 0) release(s);
                if (t128 == 0) T2((4 - NB) * 32 + kb * 2 + 1);
                if (++s == GS) { s = 0; ph ^= 1; }
            }
            if (PACEO >= 7) {
                wg_wait<0>();
                if (lane == 0) release(s == 0 ? GS - 1 : s - 1);
            }
        };
        auto out_stage = [&](const float* a, uint32_t dst) {
#pragma unroll
            for (int g = 0; g < 4; g++) {
                const int r = g * 16 + (lane >> 4) * 8 + (lane & 7), chunk = warp * 2 + ((lane >> 3) & 1);
                stmatrix_x4_t(dst + r * 128 + ((chunk ^ (lane & 7)) << 4),
                              pack_bf16(a[8 * g], a[8 * g + 1]), pack_bf16(a[8 * g + 2], a[8 * g + 3]), pack_bf16(a[8 * g + 4], a[8 * g + 5]), pack_bf16(a[8 * g + 6], a[8 * g + 7]));
            }
        };
        out_pass(IC<4>{});
        if (t128 == 0) TS(12);
        out_pass(IC<3>{});
        if (t128 == 0) TS(13);
#pragma unroll
        for (int m = 0; m < 3; m++) out_stage(c + m * 32, base + OFF_SPHI + m * 8192);
        fence_async_smem();
        __syncwarp();
        if (lane == 0) mbar_arrive(bars + B_OST);
        if (t128 == 0) T2(180);
#pragma unroll 1
        for (int kb = 0; kb < 16; kb += 3) {
            mbar_wait(bars + B_TF + kb * 8, 0);
            const uint64_t dX = mkdesc(base + OFF_KV + (kb < 12 ? kb : kb - 12) * 8192, 16, 1024, 1), dW = mkdesc(base + tail_b(kb), 16, 1024, 1);
            wg_fence();
#pragma unroll
            for (int k = 0; k < 4; k++) wgmma_o64(c, dW + k * 128, dX + k * 2, 1);
            wg_commit(); wg_wait<0>();
            if (lane == 0 && kb < 4) { mbar_arrive(bars + B_TE + kb * 8); mbar_arrive_cl(bars + B_TE + kb * 8 + peer); }
        }
        bar_sync(6, 384);
        if (t128 == 0) TS(24);
#pragma unroll
        for (int i = 0; i < 16; i++) {
            const float4 v = *reinterpret_cast<const float4*>(base_ptr + tail_b(4 + (i >> 3) + ((i >> 2) & 1) * 3) + ((i & 3) * 128 + t128) * 16);
            float* d = c + 96 + (i & 7) * 4;
            d[0] += v.x; d[1] += v.y; d[2] += v.z; d[3] += v.w;
        }
        out_stage(c + 96, base + tail_b(3));
        fence_async_smem();
        bar_sync(3, 128);
        if (t128 == 0) {
            tma_store_2d(&maps.out, base + tail_b(3), ocol, orow + 384);
            bulk_commit();
            T2(185);
            bulk_wait_all();
            T2(186);
            TS(14);
            mbar_arrive(bars + B_DONE);
            mbar_arrive_cl(bars + B_DONE + peer);
        }
    } else {
        reg_alloc<R1>();
        {
            float a0[96], a1[96];
#pragma unroll
            for (int i = 0; i < 96; i++) { a0[i] = 0.f; a1[i] = 0.f; }
            int s = 2; uint32_t ph = 0;
#pragma unroll 1
            for (int kb = 0; kb < 16; kb++) {
                mbar_wait(bars + B_PF + s * 8, ph);
                if (tid == 0 && kb == 0) TS(1);
                const uint32_t sa = base + OFF_P + s * P_STAGE;
                const uint64_t dA = mkdesc(sa + wg * 16384, 16, 1024, 1), dB = mkdesc(sa + 32768, 8192, 1024, 1);
                if (kb == 15 && wg == 1) bar_sync(7, 256);
                wg_fence();
#pragma unroll
                for (int k = 0; k < 4; k++) {
                    wgmma_n192_ss_tb(a0, dA + k * 2, dB + k * 128, 1);
                    wgmma_n192_ss_tb(a1, dA + 512 + k * 2, dB + k * 128, 1);
                }
                wg_commit();
                wg_wait<1>();
                if (lane == 0 && kb > 0) mbar_arrive(bars + B_PE + (s == 0 ? 2 : s - 1) * 8);
                if (s == 1) ph ^= 1;
                if (++s == 3) s = 0;
            }
            wg_wait<0>();
            if (lane == 0) mbar_arrive(bars + B_PE + 16);
            if (wg == 0) { bar_arrive(7, 256); mbar_wait(bars + B_PE + 8, 0); }
            else bar_sync(2, 128);
            if (tid == 0) TS(2);
            const int warp = warp_now();
#pragma unroll
            for (int blk = 0; blk < 3; blk++) {
#pragma unroll
                for (int i = 0; i < 8; i++) {
                    const int half = i >> 2, j = blk * 4 + (i & 3);
                    const float* a = half ? a1 : a0;
                    const int row = half * 64 + warp * 16 + (lane & 15);
                    stmatrix_x4(base + p_stg(wg, j >> 2) + row * 128 + ((((j * 2 + (lane >> 4)) & 7) ^ (row & 7)) << 4),
                                pack_bf16(a[8 * j], a[8 * j + 1]), pack_bf16(a[8 * j + 2], a[8 * j + 3]), pack_bf16(a[8 * j + 4], a[8 * j + 5]), pack_bf16(a[8 * j + 6], a[8 * j + 7]));
                }
                fence_async_smem();
                bar_arrive(8 + wg * 3 + blk, 160);
            }
        }
        reg_dealloc<RA>();
        const float BIAS = 64.f;
        float S0[32], S1[32], O[20];
        uint32_t P0[4][4], P1[4][4];
        int s = 0; uint32_t ph = 0;
        const uint64_t dOnes = mkdesc(base + OFF_ONES, 0, 0, 0);
        mbar_wait(bars + B_QFULL, 0);
        if (tid == 0) TS(15);
#pragma unroll 1
        for (int it = 0; it < 4; it++) {
            const uint32_t qaddr = base + OFF_Q + (it * 2 + wg) * 4096;
            const int warp = warp_now();
            if (it == 1) mbar_wait(bars + B_QF1, 0);
            uint32_t Q0[4], Q1[4], QM[4];
            {
                const int row = warp * 16 + (lane & 15);
                ldmatrix_x4(Q0, qaddr + row * 64 + (((lane >> 4) ^ ((row >> 1) & 3)) << 4));
                ldmatrix_x4(Q1, qaddr + row * 64 + (((2 + (lane >> 4)) ^ ((row >> 1) & 3)) << 4));
#pragma unroll
                for (int j = 0; j < 4; j++) { Q0[j] = pack_bf16(bf_lo(Q0[j]) * QS, bf_hi(Q0[j]) * QS); Q1[j] = pack_bf16(bf_lo(Q1[j]) * QS, bf_hi(Q1[j]) * QS); }
            }
            mbar_wait(bars + B_FULL + s * 8, ph);
            {
                const uint64_t dK = mkdesc(base + OFF_KV + s * 16384, 16, 512, 2);
                wg_fence();
                wgmma_n64_rs(S0, Q0, dK, 0); wgmma_n64_rs(S1, Q0, dK + 256, 0);
                wgmma_n64_rs(S0, Q1, dK + 2, 1); wgmma_n64_rs(S1, Q1, dK + 258, 1);
                wg_commit(); wg_wait<0>();
            }
            float m0 = S0[0], m1 = S0[2];
#pragma unroll
            for (int j = 0; j < 8; j++) {
                m0 = fmaxf(m0, fmaxf(S0[4 * j], S0[4 * j + 1])); m1 = fmaxf(m1, fmaxf(S0[4 * j + 2], S0[4 * j + 3]));
                m0 = fmaxf(m0, fmaxf(S1[4 * j], S1[4 * j + 1])); m1 = fmaxf(m1, fmaxf(S1[4 * j + 2], S1[4 * j + 3]));
            }
            m0 = fmaxf(m0, __shfl_xor_sync(~0u, m0, 1)); m0 = fmaxf(m0, __shfl_xor_sync(~0u, m0, 2));
            m1 = fmaxf(m1, __shfl_xor_sync(~0u, m1, 1)); m1 = fmaxf(m1, __shfl_xor_sync(~0u, m1, 2));
            float n0 = -m0 - BIAS, n1 = -m1 - BIAS;
            {
                const uint32_t pk = pack_bf16(n0, n1);
                n0 = bf_lo(pk); n1 = bf_hi(pk);
                const uint32_t slot = qaddr + warp * 1024 + lane * 16;
                sts128(slot, (lane & 3) ? 0u : (pk & 0xffffu), (lane & 3) ? 0u : (pk >> 16), 0u, 0u);
                asm volatile("ld.shared.v4.b32 {%0,%1,%2,%3}, [%4];" : "=r"(QM[0]), "=r"(QM[1]), "=r"(QM[2]), "=r"(QM[3]) : "r"(slot) : "memory");
            }
#pragma unroll
            for (int j = 0; j < 32; j++) { S0[j] += (j & 2) ? n1 : n0; S1[j] += (j & 2) ? n1 : n0; }
#pragma unroll
            for (int j = 0; j < 20; j++) O[j] = 0.f;
            auto softmax = [&](float (&S)[32], uint32_t (&PP)[4][4]) {
#pragma unroll
                for (int q = 0; q < 16; q++) {
                    if ((POLYMASK >> q) & 1) PP[q >> 2][q & 3] = exp2_pair(S[2 * q], S[2 * q + 1]);
                    else PP[q >> 2][q & 3] = pack_bf16(ex2(S[2 * q]), ex2(S[2 * q + 1]));
                }
            };
            auto pv = [&](int st, const int half, uint32_t (&PP)[4][4]) {
                const uint32_t vaddr = base + OFF_KV + st * 16384 + 8192;
                const uint64_t dV0 = mkdesc(vaddr, (base + OFF_ONES) - vaddr, 512, 2);
#pragma unroll
                for (int k4 = 0; k4 < 4; k4++) { const int kk = half * 4 + k4; wgmma_n40_rs_tb(O, PP[k4], dV0 + (uint64_t)kk * 64 - ((uint64_t)kk * 64 << 16), 1); }
            };
            auto qkpv = [&](float (&S)[32], uint64_t dK, int st, const int half, uint32_t (&PP)[4][4]) {
                const uint32_t vaddr = base + OFF_KV + st * 16384 + 8192;
                const uint64_t dV0 = mkdesc(vaddr, (base + OFF_ONES) - vaddr, 512, 2);
                auto pk = [&](int k4) { const int kk = half * 4 + k4; wgmma_n40_rs_tb(O, PP[k4], dV0 + (uint64_t)kk * 64 - ((uint64_t)kk * 64 << 16), 1); };
                wgmma_n64_rs(S, QM, dOnes, 0);
                pk(0);
                wgmma_n64_rs(S, Q0, dK, 1);
                pk(1);
                wgmma_n64_rs(S, Q1, dK + 2, 1);
                pk(2);
                pk(3);
            };
            softmax(S0, P0);
            int s2 = s + 1; uint32_t ph2 = ph; if (s2 == NS) { s2 = 0; ph2 ^= 1; }
            mbar_wait(bars + B_FULL + s2 * 8, ph2);
#pragma unroll 1
            for (int tt = 0; tt < 15 / UNR; tt++) {
                int sp = 0;
#pragma unroll
                for (int u = 0; u < UNR; u++) {
                    const uint64_t dK = mkdesc(base + OFF_KV + s2 * 16384, 16, 512, 2);
                    wg_fence();
                    qkpv(S0, dK, s, 0, P0);
                    wg_commit();
                    if (u > 0) { wg_wait<1>(); if (lane == 0) mbar_arrive(bars + B_EMPTY + sp * 8); }
                    softmax(S1, P1);
                    wg_fence();
                    qkpv(S1, dK + 256, s, 1, P1);
                    wg_commit();
                    wg_wait<1>();
                    softmax(S0, P0);
                    sp = s; s = s2; ph = ph2;
                    if (u < UNR - 1 || tt < 15 / UNR - 1) { if (++s2 == NS) { s2 = 0; ph2 ^= 1; } }
                    mbar_wait(bars + B_FULL + s2 * 8, ph2);
                    if (u == UNR - 1) { wg_wait<0>(); if (lane == 0) mbar_arrive(bars + B_EMPTY + sp * 8); }
                }
            }
            wg_fence();
            pv(s, 0, P0);
            wg_commit();
            softmax(S1, P1);
            wg_fence();
            pv(s, 1, P1);
            wg_commit(); wg_wait<0>();
            if (lane == 0) mbar_arrive(bars + B_EMPTY + s * 8);
            if (++s == NS) { s = 0; ph ^= 1; }
            float chk = 0.f;
#pragma unroll
            for (int j = 0; j < 16; j++) chk = fmaxf(chk, fabsf(O[j]));
            const bool bad = !(O[16] < 1e30f && O[16] > 1e-30f && O[18] < 1e30f && O[18] > 1e-30f && chk < 3e38f) ||
                             (O[0] + O[1] + O[2] + O[3] + O[4] + O[5] + O[6] + O[7] + O[8] + O[9] + O[10] + O[11] + O[12] + O[13] + O[14] + O[15]) !=
                             (O[0] + O[1] + O[2] + O[3] + O[4] + O[5] + O[6] + O[7] + O[8] + O[9] + O[10] + O[11] + O[12] + O[13] + O[14] + O[15]);
            const int row0 = quarter * 512 + it * 128 + wg * 64, wrp = warp_now();
            if (__any_sync(~0u, bar_or(1 + wg, 128, bad))) {
                attn_exact(head, row0, qaddr, tid & 127);
            } else {
                const float2* gs = reinterpret_cast<const float2*>(base_ptr + OFF_GATE) + it * 128 + wg * 64 + wrp * 16 + (lane >> 2);
                const float i0 = gs[0].y / O[16], i1 = gs[8].y / O[18];
                const int row = wrp * 16 + (lane & 15);
#pragma unroll
                for (int j = 0; j < 2; j++)
                    stmatrix_x4(qaddr + row * 64 + (((j * 2 + (lane >> 4)) ^ ((row >> 1) & 3)) << 4),
                                pack_bf16(O[8 * j] * i0, O[8 * j + 1] * i0), pack_bf16(O[8 * j + 2] * i1, O[8 * j + 3] * i1),
                                pack_bf16(O[8 * j + 4] * i0, O[8 * j + 5] * i0), pack_bf16(O[8 * j + 6] * i1, O[8 * j + 7] * i1));
            }
            fence_async_smem();
            mbar_arrive(bars + B_ORDY + wg * 8);
            if (tid == 0) TS(16 + it);
            if (tid == 0) T2(128 + it);
        }
#pragma unroll 1
        for (int kb = 1 + wg; kb < 16; kb += 3) {
            mbar_wait(bars + B_TF + kb * 8, 0);
            const uint64_t dX = mkdesc(base + OFF_KV + (kb < 12 ? kb : kb - 12) * 8192, 16, 1024, 1), dW = mkdesc(base + tail_b(kb), 16, 1024, 1);
            wg_fence();
#pragma unroll
            for (int k = 0; k < 4; k++) wgmma_t64(S0, dW + k * 128, dX + k * 2, kb > 2 || k > 0);
            wg_commit(); wg_wait<0>();
            if (lane == 0 && kb < 4) { mbar_arrive(bars + B_TE + kb * 8); mbar_arrive_cl(bars + B_TE + kb * 8 + peer); }
        }
        bar_sync(1 + wg, 128);
#pragma unroll
        for (int i = 0; i < 8; i++)
            *reinterpret_cast<float4*>(base_ptr + tail_b(4 + wg + (i >> 2) * 3) + ((i & 3) * 128 + (tid & 127)) * 16) = make_float4(S0[4 * i], S0[4 * i + 1], S0[4 * i + 2], S0[4 * i + 3]);
        bar_arrive(6, 384);
        if ((tid & 127) == 0) mbar_arrive(bars + B_DONE);
    }
}

typedef CUresult (*PFN_encodeTiled)(CUtensorMap*, CUtensorMapDataType, cuuint32_t, void*, const cuuint64_t*, const cuuint64_t*, const cuuint32_t*,
                                    const cuuint32_t*, CUtensorMapInterleave, CUtensorMapSwizzle, CUtensorMapL2promotion, CUtensorMapFloatOOBfill);

CUtensorMap make_map(PFN_encodeTiled enc, const void* ptr, uint64_t inner, uint64_t outer, uint32_t box_inner, uint32_t box_outer, CUtensorMapSwizzle swz) {
    CUtensorMap m;
    cuuint64_t dims[2] = {inner, outer};
    cuuint64_t strides[1] = {inner * 2};
    cuuint32_t box[2] = {box_inner, box_outer};
    cuuint32_t es[2] = {1, 1};
    enc(&m, CU_TENSOR_MAP_DATA_TYPE_BFLOAT16, 2, const_cast<void*>(ptr), dims, strides, box, es, CU_TENSOR_MAP_INTERLEAVE_NONE, swz,
        CU_TENSOR_MAP_L2_PROMOTION_L2_128B, CU_TENSOR_MAP_FLOAT_OOB_FILL_NONE);
    return m;
}

}

extern "C" void kernel_launch(void* const* d_in, const int* in_sizes, int n_in, void* d_out, int out_size) {
    (void)in_sizes; (void)n_in; (void)out_size;
    static PFN_encodeTiled enc = nullptr;
    static void *p_qkv = nullptr, *p_act = nullptr;
    if (!enc) {
        void* p = nullptr;
        cudaDriverEntryPointQueryResult qr;
        cudaGetDriverEntryPoint("cuTensorMapEncodeTiled", &p, cudaEnableDefault, &qr);
        enc = (PFN_encodeTiled)p;
        cudaGetSymbolAddress(&p_qkv, g_qkv);
        cudaGetSymbolAddress(&p_act, g_act);
        cudaFuncSetAttribute(k2_fused, cudaFuncAttributeMaxDynamicSharedMemorySize, K2_SMEM);
    }
    const auto SW128 = CU_TENSOR_MAP_SWIZZLE_128B;
    const auto SW64 = CU_TENSOR_MAP_SWIZZLE_64B;
    K2Maps m2;
    m2.x1 = make_map(enc, d_in[0], 1024, 2048, 64, 256, SW128);
    m2.w1 = make_map(enc, d_in[5], 3072, 1024, 64, 64, SW128);
    m2.o1 = make_map(enc, p_qkv, 3072, 2048, 64, 128, SW128);
    m2.kv = make_map(enc, p_qkv, 3072, 2048, 32, 128, SW64);
    m2.ob = make_map(enc, p_act, 2048, 2048, 32, 64, SW64);
    m2.x = make_map(enc, d_in[0], 1024, 2048, 64, 128, SW128);
    m2.wa = make_map(enc, d_in[1], 3072, 1024, 64, 64, SW128);
    m2.phi = make_map(enc, d_in[2], 32, 1024, 32, 64, SW64);
    m2.act = make_map(enc, p_act, 2048, 2048, 64, 64, SW128);
    m2.woa = make_map(enc, d_in[3], 1024, 1024, 64, 64, SW128);
    m2.wob = make_map(enc, d_in[6], 1024, 1024, 64, 64, SW128);
    m2.out = make_map(enc, d_out, 1024, 2048, 64, 64, SW128);
    m2.oa = make_map(enc, p_act, 2048, 2048, 32, 128, SW64);

    cudaStream_t st = cudaStreamPerThread;
    cudaLaunchConfig_t cfg = {};
    cfg.gridDim = dim3(128); cfg.blockDim = dim3(512); cfg.dynamicSmemBytes = K2_SMEM; cfg.stream = st;
    cudaLaunchAttribute at[1];
    at[0].id = cudaLaunchAttributeClusterDimension;
    at[0].val.clusterDim.x = 2; at[0].val.clusterDim.y = 1; at[0].val.clusterDim.z = 1;
    cfg.attrs = at; cfg.numAttrs = 1;
    cudaLaunchKernelEx(&cfg, k2_fused, m2, (const __nv_bfloat16*)d_in[0], (const __nv_bfloat16*)d_in[7]);
}
```
